```python
import torch

def _softmax(x, axis=-1):
    return torch.softmax(x, dim=axis)
def _gelu(x):
    return torch.nn.functional.gelu(x, approximate="tanh")
def _silu(x):
    return torch.nn.functional.silu(x)
def _sigmoid(x):
    return torch.sigmoid(x)
def _layernorm(x, axis=-1, eps=1e-5):
    m = x.mean(dim=axis, keepdim=True)
    v = x.var(dim=axis, keepdim=True, unbiased=False)
    return (x - m) / torch.sqrt(v + eps)
def _scatter_add(tgt, idx, src, axis=0):
    return tgt.clone().index_add_(axis, idx, src)
def _segment_sum(src, seg, n):
    out = torch.zeros((n,) + src.shape[1:], dtype=src.dtype)
    return out.index_add_(0, seg, src)
def _pad(x, pw):
    flat = tuple(v for pair in reversed(pw) for v in pair)
    return torch.nn.functional.pad(x, flat)

kernel_name = 'gated_mix__ssm_conv_s4d__swiglu_ffn__prompt'

def setup_inputs():

    _w = (lambda a: (lambda t: t.to(torch.bfloat16) if t.is_floating_point() else t)(torch.as_tensor(a)))
    def _A_setup():
        Bsz, L, D, N = 1, 2048, 512, 128
        return {
            "u": _w((lambda *s: torch.randn(*s, dtype=torch.bfloat16) * 0.05)(Bsz, L, D)),
            "log_A_real": _w((lambda *s: torch.randn(*s, dtype=torch.bfloat16) * 6.4)(D, N) * 0.5),
            "A_imag": _w((lambda *s: torch.randn(*s, dtype=torch.bfloat16) * 0.05)(D, N) * 3.14),
            "C_real": _w((lambda *s: torch.randn(*s, dtype=torch.bfloat16) * 0.05)(D, N) / N ** 0.5),
            "C_imag": _w((lambda *s: torch.randn(*s, dtype=torch.bfloat16) * 0.05)(D, N) / N ** 0.5),
            "log_dt": _w((lambda *s: torch.randn(*s, dtype=torch.bfloat16) * 0.05)(D) * 0.5 - 4.0),
            "D_skip": _w((lambda *s: torch.randn(*s, dtype=torch.bfloat16) * 0.05)(D)),
        }
    _A_in = _A_setup()

    def _B_setup():
        B, S, D, F = 1, 2048, 512, 1376
        return {
            "x": _w((lambda *s: torch.randn(*s, dtype=torch.bfloat16) * 0.05)(B, S, D)),
            "w_gate": _w((lambda *s: torch.randn(*s, dtype=torch.bfloat16) * 0.05)(D, F)),
            "w_up": _w((lambda *s: torch.randn(*s, dtype=torch.bfloat16) * 0.05)(D, F)),
            "w_down": _w((lambda *s: torch.randn(*s, dtype=torch.bfloat16) * 0.05)(F, D)),
        }
    _B_in = _B_setup()

    return {
        "A_u": _A_in["u"],
        "A_log_A_real": _A_in["log_A_real"],
        "A_A_imag": _A_in["A_imag"],
        "A_C_real": _A_in["C_real"],
        "A_C_imag": _A_in["C_imag"],
        "A_log_dt": _A_in["log_dt"],
        "A_D_skip": _A_in["D_skip"],
        "B_x": _B_in["x"],
        "B_w_gate": _B_in["w_gate"],
        "B_w_up": _B_in["w_up"],
        "B_w_down": _B_in["w_down"],
        "gate_w": _w((lambda *s: torch.randn(*s, dtype=torch.bfloat16) * 0.05)(512) * 16.0),
    }

def reference(A_u, A_log_A_real, A_A_imag, A_C_real, A_C_imag, A_log_dt, A_D_skip, B_x, B_w_gate, B_w_up, B_w_down, gate_w):
    def _A_ref(u, log_A_real, A_imag, C_real, C_imag, log_dt, D_skip):
        L = u.shape[1]
        dt = torch.exp(log_dt)
        A = -torch.exp(log_A_real) + 1j * A_imag
        C = (C_real + 1j * C_imag) * dt[:, None]
        pos = (lambda x, dt: x.to(dt))(torch.arange(L), log_dt.dtype)
        P = torch.exp((A * dt[:, None])[:, :, None] * pos[None, None, :])
        K = 2.0 * torch.einsum("dn,dnl->dl", C, P).real
        L2 = 2 * L
        u_t = (lambda x, *d: x.permute(*d))(u, 0, 2, 1)
        Kf = (lambda x, *a, **k: torch.fft.rfft(x.float(), *a, **k))(K, L2)
        Uf = (lambda x, *a, **k: torch.fft.rfft(x.float(), *a, **k))(u_t, L2)
        y = (lambda x, *a, **k: torch.fft.irfft(x, *a, **k).to(torch.bfloat16))(Uf * Kf[None, :, :], L2)[:, :, :L]
        y = (lambda x, *d: x.permute(*d))(y, 0, 2, 1)
        return y + u * D_skip[None, None, :]

    def _B_ref(x, w_gate, w_up, w_down):
        g = _silu(x @ w_gate)
        u = x @ w_up
        return (g * u) @ w_down

    x = A_u
    g = _sigmoid((x * gate_w).sum(-1, keepdims=True))
    a = _A_ref(x, A_log_A_real, A_A_imag, A_C_real, A_C_imag, A_log_dt, A_D_skip)
    b = _B_ref(x, B_w_gate, B_w_up, B_w_down)
    return g * a + (1 - g) * b
```

```cpp
#include <cuda_runtime.h>
#include <cuda_bf16.h>
#include <cuda.h>
#include <stdint.h>

namespace {

constexpr int kL = 2048, kD = 512, kF = 1376;
constexpr int kTok1 = 176;
constexpr int kNumFt = 22;
constexpr int kThreads = 512;

constexpr uint32_t kStage = 27648, kStageX = 16384;
constexpr uint32_t kOffU = 138240, kOffTaps = 155648, kOffV = 172032, kOffBar = 213248;
constexpr uint32_t kOffSpare = 214016, kOffGate = 230400, kSmemBytes = 231424;
constexpr uint32_t kVChan = 10304, kPart = 2576, kXRow = 1040;
constexpr int kNW = 13, kNH = 6;
constexpr uint32_t kV3e = 0, kV3o = 97 * 16, kV5e = 193 * 16, kV5o = 290 * 16;
constexpr uint32_t kV7e = 386 * 16, kV7o = 450 * 16, kV9e = 514 * 16;
constexpr uint32_t kTapA = 2176, kTapB = kTapA + 384, kTapC = kTapB + 384, kTapK = kTapC + 576;

constexpr int B_FULL1 = 0, B_EMPTY1 = 5, B_FULLW = 10, B_EMPTYW = 23, B_FULLH = 36, B_EMPTYH = 42;
constexpr int B_XR = 48, B_U = 49, B_A = 50, B_RDYA = 51, B_RDYB = 52, B_RDYC = 53, B_COUNT = 54;
constexpr int NB_KGEN = 1, NB_P1 = 2, NB_H = 3, NB_WG2 = 5, NB_CONV = 6, NB_OUT = 7;
constexpr int C_U = 0, C_H = 1, C_A = 13, C_DONE = 21, C_COUNT = 22;

__device__ __align__(1024) uint8_t g_H[kNumFt * kL * 128];
__device__ __align__(1024) uint8_t g_uT[128 * kD * 32];
__device__ __align__(1024) uint8_t g_aT[8 * 16 * 64 * 256];
__device__ __align__(1024) float2 g_gate[kL];
__device__ unsigned g_cnt[C_COUNT * 32];

#define STAMP(i) do { } while (0)
#define PROF_PARAM
#define PROF_ARG

__host__ __device__ constexpr uint32_t wd_slot(int s) {
  return s < 2 ? kOffSpare + s * 8192 : (s < 12 ? (s - 2) * 8192 : kOffV + 32768);
}
__host__ __device__ constexpr uint32_t h_slot(int s) {
  return s < 2 ? kOffV + s * 16384 : (s < 5 ? 3 * kStage + (s - 2) * 16384 : kOffTaps);
}

__device__ __forceinline__ void mbar_init(uint32_t b, uint32_t c) {
  asm volatile("mbarrier.init.shared::cta.b64 [%0], %1;" ::"r"(b), "r"(c) : "memory");
}
__device__ __forceinline__ void mbar_expect(uint32_t b, uint32_t tx) {
  asm volatile("mbarrier.arrive.expect_tx.shared::cta.b64 _, [%0], %1;" ::"r"(b), "r"(tx) : "memory");
}
__device__ __forceinline__ void mbar_arrive(uint32_t b) {
  asm volatile("mbarrier.arrive.shared::cta.b64 _, [%0];" ::"r"(b) : "memory");
}
__device__ __forceinline__ void mbar_arrive_cta(uint32_t b, uint32_t cta) {
  asm volatile("{\n.reg .b32 r;\nmapa.shared::cluster.u32 r, %0, %1;\n"
               "mbarrier.arrive.shared::cluster.b64 _, [r];\n}" ::"r"(b), "r"(cta) : "memory");
}
__device__ __forceinline__ void mbar_wait(uint32_t b, uint32_t parity) {
  asm volatile("{\n.reg .pred p;\n.reg .u32 n;\nmov.u32 n, 0;\n"
               "W_LOOP:\n"
               "mbarrier.try_wait.parity.shared::cta.b64 p, [%0], %1, 2000;\n"
               "@p bra W_DONE;\n"
               "add.u32 n, n, 1;\nsetp.lt.u32 p, n, 1000000;\n@p bra W_LOOP;\ntrap;\n"
               "W_DONE:\n}" ::"r"(b), "r"(parity) : "memory");
}
__device__ __forceinline__ void bar_sync(int id, int n) { asm volatile("bar.sync %0, %1;" ::"r"(id), "r"(n) : "memory"); }
__device__ __forceinline__ void bar_arrive(int id, int n) { asm volatile("bar.arrive %0, %1;" ::"r"(id), "r"(n) : "memory"); }
__device__ __forceinline__ void fence_async_smem() { asm volatile("fence.proxy.async.shared::cta;" ::: "memory"); }
__device__ __forceinline__ void fence_async_all() { asm volatile("fence.proxy.async;" ::: "memory"); }
__device__ __forceinline__ void cnt_add(int c) {
  asm volatile("red.release.gpu.global.add.u32 [%0], 1;" ::"l"(&g_cnt[c * 32]) : "memory");
}
__device__ __forceinline__ void cnt_wait(int c, unsigned target) {
  unsigned v, n = 0;
  do {
    asm volatile("ld.acquire.gpu.global.u32 %0, [%1];" : "=r"(v) : "l"(&g_cnt[c * 32]) : "memory");
    if (++n > 4000000u) __trap();
  } while (v < target);
}
__device__ __forceinline__ void cnt_done() {
  unsigned v = atomicAdd(&g_cnt[C_DONE * 32], 1u);
  if (v == 255u) {
    for (int i = 0; i < C_COUNT; i++) g_cnt[i * 32] = 0u;
  }
}
__device__ __forceinline__ void tma2d(uint32_t dst, const CUtensorMap* m, int c0, int c1, uint32_t bar) {
  asm volatile("cp.async.bulk.tensor.2d.shared::cluster.global.mbarrier::complete_tx::bytes [%0], [%1, {%3, %4}], [%2];"
               ::"r"(dst), "l"(m), "r"(bar), "r"(c0), "r"(c1) : "memory");
}
__device__ __forceinline__ void tma2d_mc(uint32_t dst, const CUtensorMap* m, int c0, int c1, uint32_t bar) {
  asm volatile("cp.async.bulk.tensor.2d.shared::cluster.global.mbarrier::complete_tx::bytes.multicast::cluster"
               " [%0], [%1, {%3, %4}], [%2], %5;"
               ::"r"(dst), "l"(m), "r"(bar), "r"(c0), "r"(c1), "h"((uint16_t)3) : "memory");
}
__device__ __forceinline__ void tma2d_store(const CUtensorMap* m, uint32_t src, int c0, int c1) {
  asm volatile("cp.async.bulk.tensor.2d.global.shared::cta.bulk_group [%0, {%2, %3}], [%1];"
               ::"l"(m), "r"(src), "r"(c0), "r"(c1) : "memory");
}
__device__ __forceinline__ void bulk_load(uint32_t dst, const void* src, uint32_t bytes, uint32_t bar) {
  asm volatile("cp.async.bulk.shared::cluster.global.mbarrier::complete_tx::bytes [%0], [%1], %2, [%3];"
               ::"r"(dst), "l"(src), "r"(bytes), "r"(bar) : "memory");
}
__device__ __forceinline__ void bulk_load_mc(uint32_t dst, const void* src, uint32_t bytes, uint32_t bar) {
  asm volatile("cp.async.bulk.shared::cluster.global.mbarrier::complete_tx::bytes.multicast::cluster [%0], [%1], %2, [%3], %4;"
               ::"r"(dst), "l"(src), "r"(bytes), "r"(bar), "h"((uint16_t)3) : "memory");
}
__device__ __forceinline__ void bulk_store(void* dst, uint32_t src, uint32_t bytes) {
  asm volatile("cp.async.bulk.global.shared::cta.bulk_group [%0], [%1], %2;" ::"l"(dst), "r"(src), "r"(bytes) : "memory");
}
__device__ __forceinline__ void bulk_commit() { asm volatile("cp.async.bulk.commit_group;" ::: "memory"); }
__device__ __forceinline__ void bulk_wait_read() { asm volatile("cp.async.bulk.wait_group.read 0;" ::: "memory"); }
__device__ __forceinline__ void bulk_wait() { asm volatile("cp.async.bulk.wait_group 0;" ::: "memory"); }

__device__ __forceinline__ void wg_fence() { asm volatile("wgmma.fence.sync.aligned;" ::: "memory"); }
__device__ __forceinline__ void wg_commit() { asm volatile("wgmma.commit_group.sync.aligned;" ::: "memory"); }
template <int N> __device__ __forceinline__ void wg_wait() { asm volatile("wgmma.wait_group.sync.aligned %0;" ::"n"(N) : "memory"); }
__device__ __forceinline__ uint64_t make_desc(uint32_t addr, uint32_t sbo, uint32_t swizzle) {
  return (uint64_t)((addr >> 4) | (1u << 16)) | ((uint64_t)((sbo >> 4) | (swizzle << 30)) << 32);
}

__device__ __forceinline__ void wgmma_n176(float (&d)[88], uint64_t da, uint64_t db, int acc) {
  asm volatile(
      "{\n.reg .pred p;\nsetp.ne.b32 p, %90, 0;\n"
      "wgmma.mma_async.sync.aligned.m64n176k16.f32.bf16.bf16 {"
      "%0,%1,%2,%3,%4,%5,%6,%7,%8,%9,%10,%11,%12,%13,%14,%15,"
      "%16,%17,%18,%19,%20,%21,%22,%23,%24,%25,%26,%27,%28,%29,%30,%31,"
      "%32,%33,%34,%35,%36,%37,%38,%39,%40,%41,%42,%43,%44,%45,%46,%47,"
      "%48,%49,%50,%51,%52,%53,%54,%55,%56,%57,%58,%59,%60,%61,%62,%63,"
      "%64,%65,%66,%67,%68,%69,%70,%71,%72,%73,%74,%75,%76,%77,%78,%79,"
      "%80,%81,%82,%83,%84,%85,%86,%87"
      "}, %88, %89, p, 1, 1, 1, 0;\n}\n"
      : "+f"(d[0]), "+f"(d[1]), "+f"(d[2]), "+f"(d[3]), "+f"(d[4]), "+f"(d[5]), "+f"(d[6]), "+f"(d[7]),
        "+f"(d[8]), "+f"(d[9]), "+f"(d[10]), "+f"(d[11]), "+f"(d[12]), "+f"(d[13]), "+f"(d[14]), "+f"(d[15]),
        "+f"(d[16]), "+f"(d[17]), "+f"(d[18]), "+f"(d[19]), "+f"(d[20]), "+f"(d[21]), "+f"(d[22]), "+f"(d[23]),
        "+f"(d[24]), "+f"(d[25]), "+f"(d[26]), "+f"(d[27]), "+f"(d[28]), "+f"(d[29]), "+f"(d[30]), "+f"(d[31]),
        "+f"(d[32]), "+f"(d[33]), "+f"(d[34]), "+f"(d[35]), "+f"(d[36]), "+f"(d[37]), "+f"(d[38]), "+f"(d[39]),
        "+f"(d[40]), "+f"(d[41]), "+f"(d[42]), "+f"(d[43]), "+f"(d[44]), "+f"(d[45]), "+f"(d[46]), "+f"(d[47]),
        "+f"(d[48]), "+f"(d[49]), "+f"(d[50]), "+f"(d[51]), "+f"(d[52]), "+f"(d[53]), "+f"(d[54]), "+f"(d[55]),
        "+f"(d[56]), "+f"(d[57]), "+f"(d[58]), "+f"(d[59]), "+f"(d[60]), "+f"(d[61]), "+f"(d[62]), "+f"(d[63]),
        "+f"(d[64]), "+f"(d[65]), "+f"(d[66]), "+f"(d[67]), "+f"(d[68]), "+f"(d[69]), "+f"(d[70]), "+f"(d[71]),
        "+f"(d[72]), "+f"(d[73]), "+f"(d[74]), "+f"(d[75]), "+f"(d[76]), "+f"(d[77]), "+f"(d[78]), "+f"(d[79]),
        "+f"(d[80]), "+f"(d[81]), "+f"(d[82]), "+f"(d[83]), "+f"(d[84]), "+f"(d[85]), "+f"(d[86]), "+f"(d[87])
      : "l"(da), "l"(db), "r"(acc));
}

__device__ __forceinline__ void wgmma_n128(float (&d)[64], uint64_t da, uint64_t db, int acc) {
  asm volatile(
      "{\n.reg .pred p;\nsetp.ne.b32 p, %66, 0;\n"
      "wgmma.mma_async.sync.aligned.m64n128k16.f32.bf16.bf16 {"
      "%0,%1,%2,%3,%4,%5,%6,%7,%8,%9,%10,%11,%12,%13,%14,%15,"
      "%16,%17,%18,%19,%20,%21,%22,%23,%24,%25,%26,%27,%28,%29,%30,%31,"
      "%32,%33,%34,%35,%36,%37,%38,%39,%40,%41,%42,%43,%44,%45,%46,%47,"
      "%48,%49,%50,%51,%52,%53,%54,%55,%56,%57,%58,%59,%60,%61,%62,%63"
      "}, %64, %65, p, 1, 1, 1, 0;\n}\n"
      : "+f"(d[0]), "+f"(d[1]), "+f"(d[2]), "+f"(d[3]), "+f"(d[4]), "+f"(d[5]), "+f"(d[6]), "+f"(d[7]),
        "+f"(d[8]), "+f"(d[9]), "+f"(d[10]), "+f"(d[11]), "+f"(d[12]), "+f"(d[13]), "+f"(d[14]), "+f"(d[15]),
        "+f"(d[16]), "+f"(d[17]), "+f"(d[18]), "+f"(d[19]), "+f"(d[20]), "+f"(d[21]), "+f"(d[22]), "+f"(d[23]),
        "+f"(d[24]), "+f"(d[25]), "+f"(d[26]), "+f"(d[27]), "+f"(d[28]), "+f"(d[29]), "+f"(d[30]), "+f"(d[31]),
        "+f"(d[32]), "+f"(d[33]), "+f"(d[34]), "+f"(d[35]), "+f"(d[36]), "+f"(d[37]), "+f"(d[38]), "+f"(d[39]),
        "+f"(d[40]), "+f"(d[41]), "+f"(d[42]), "+f"(d[43]), "+f"(d[44]), "+f"(d[45]), "+f"(d[46]), "+f"(d[47]),
        "+f"(d[48]), "+f"(d[49]), "+f"(d[50]), "+f"(d[51]), "+f"(d[52]), "+f"(d[53]), "+f"(d[54]), "+f"(d[55]),
        "+f"(d[56]), "+f"(d[57]), "+f"(d[58]), "+f"(d[59]), "+f"(d[60]), "+f"(d[61]), "+f"(d[62]), "+f"(d[63])
      : "l"(da), "l"(db), "r"(acc));
}

__device__ __forceinline__ void mma_bf16(float (&c)[4], uint32_t a0, uint32_t a1, uint32_t a2, uint32_t a3,
                                         uint32_t b0, uint32_t b1) {
  asm volatile("mma.sync.aligned.m16n8k16.row.col.f32.bf16.bf16.f32 {%0,%1,%2,%3}, {%4,%5,%6,%7}, {%8,%9}, {%0,%1,%2,%3};"
               : "+f"(c[0]), "+f"(c[1]), "+f"(c[2]), "+f"(c[3])
               : "r"(a0), "r"(a1), "r"(a2), "r"(a3), "r"(b0), "r"(b1));
}
__device__ __forceinline__ void ldsm4(uint32_t (&r)[4], uint32_t a) {
  asm volatile("ldmatrix.sync.aligned.m8n8.x4.shared.b16 {%0,%1,%2,%3}, [%4];"
               : "=r"(r[0]), "=r"(r[1]), "=r"(r[2]), "=r"(r[3]) : "r"(a) : "memory");
}
__device__ __forceinline__ void ldsm4t(uint32_t (&r)[4], uint32_t a) {
  asm volatile("ldmatrix.sync.aligned.m8n8.x4.trans.shared.b16 {%0,%1,%2,%3}, [%4];"
               : "=r"(r[0]), "=r"(r[1]), "=r"(r[2]), "=r"(r[3]) : "r"(a) : "memory");
}
__device__ __forceinline__ void stsm4t(uint32_t a, uint32_t r0, uint32_t r1, uint32_t r2, uint32_t r3) {
  asm volatile("stmatrix.sync.aligned.m8n8.x4.trans.shared.b16 [%0], {%1,%2,%3,%4};"
               ::"r"(a), "r"(r0), "r"(r1), "r"(r2), "r"(r3) : "memory");
}
__device__ __forceinline__ uint32_t lds32(uint32_t a) {
  uint32_t v; asm volatile("ld.shared.b32 %0, [%1];" : "=r"(v) : "r"(a) : "memory"); return v;
}
__device__ __forceinline__ float ldsf(uint32_t a) { return __uint_as_float(lds32(a)); }
__device__ __forceinline__ float lds_bf16(uint32_t a) {
  uint16_t v; asm volatile("ld.shared.b16 %0, [%1];" : "=h"(v) : "r"(a) : "memory");
  return __uint_as_float((uint32_t)v << 16);
}
__device__ __forceinline__ uint2 lds64(uint32_t a) {
  uint2 v; asm volatile("ld.shared.v2.b32 {%0,%1}, [%2];" : "=r"(v.x), "=r"(v.y) : "r"(a) : "memory"); return v;
}
__device__ __forceinline__ uint4 lds128(uint32_t a) {
  uint4 v; asm volatile("ld.shared.v4.b32 {%0,%1,%2,%3}, [%4];" : "=r"(v.x), "=r"(v.y), "=r"(v.z), "=r"(v.w) : "r"(a) : "memory");
  return v;
}
__device__ __forceinline__ void sts32(uint32_t a, uint32_t v) { asm volatile("st.shared.b32 [%0], %1;" ::"r"(a), "r"(v) : "memory"); }
__device__ __forceinline__ void sts64(uint32_t a, uint32_t x, uint32_t y) {
  asm volatile("st.shared.v2.b32 [%0], {%1,%2};" ::"r"(a), "r"(x), "r"(y) : "memory");
}
__device__ __forceinline__ void sts128(uint32_t a, uint32_t x, uint32_t y, uint32_t z, uint32_t w) {
  asm volatile("st.shared.v4.b32 [%0], {%1,%2,%3,%4};" ::"r"(a), "r"(x), "r"(y), "r"(z), "r"(w) : "memory");
}
__device__ __forceinline__ uint32_t pack2(float lo, float hi) {
  uint32_t r; asm("cvt.rn.bf16x2.f32 %0, %1, %2;" : "=r"(r) : "f"(hi), "f"(lo)); return r;
}
__device__ __forceinline__ float bf_lo(uint32_t v) { return __uint_as_float(v << 16); }
__device__ __forceinline__ float bf_hi(uint32_t v) { return __uint_as_float(v & 0xffff0000u); }
__device__ __forceinline__ float bf_round(float v) { return __bfloat162float(__float2bfloat16_rn(v)); }
__device__ __forceinline__ float ldg_bf16(const __nv_bfloat16* p) {
  return __uint_as_float((uint32_t)__ldg(reinterpret_cast<const unsigned short*>(p)) << 16);
}
__device__ __forceinline__ float2 cmul(float2 a, float2 b) {
  return make_float2(fmaf(a.x, b.x, -a.y * b.y), fmaf(a.x, b.y, a.y * b.x));
}
__device__ __forceinline__ float2 cexp_p(float zr2, float zi, float p) {
  float m; asm("ex2.approx.ftz.f32 %0, %1;" : "=f"(m) : "f"(zr2 * p));
  const float x = zi * p;
  const float k = rintf(x * 0.15915494309189535f);
  float r = fmaf(-k, 6.2831854820251465f, x);
  r = fmaf(-k, -1.7484555314695172e-7f, r);
  return make_float2(m * __cosf(r), m * __sinf(r));
}
__device__ __forceinline__ void sts_row(uint32_t a, const float2 (&v)[8]) {
  sts128(a, pack2(v[0].x, v[1].x), pack2(v[2].x, v[3].x), pack2(v[4].x, v[5].x), pack2(v[6].x, v[7].x));
  sts128(a + 512, pack2(v[0].y, v[1].y), pack2(v[2].y, v[3].y), pack2(v[4].y, v[5].y), pack2(v[6].y, v[7].y));
}
__device__ __forceinline__ uint32_t k_index(int p) {
  const int a = p >> 7, b = p & 7;
  const int j = p < 256 ? a * 8 + b : (p < 512 ? 8 + 4 * a + (b >> 1) : (p < 1024 ? 16 + 2 * a + (b >> 2) : 24 + a));
  return p == 2048 ? 2560u : (uint32_t)((((p >> 3) & 15) * 40 + j) * 4);
}

struct Params {
  const __nv_bfloat16 *x, *log_a, *a_im, *c_re, *c_im, *log_dt, *d_skip, *gate_w;
};

__device__ __forceinline__ void kgen_task(uint32_t st, int lane, float lar, float aim, float cre, float cim, float ldt) {
  const float dt = bf_round(expf(ldt));
  const float zr2 = -bf_round(expf(lar)) * dt * 1.4426950408889634f;
  const float zi = aim * dt;
  const float2 w1 = cexp_p(zr2, zi, 1.f), w8 = cexp_p(zr2, zi, 8.f), w128 = cexp_p(zr2, zi, 128.f);
  const float2 c = make_float2(2.f * cre * dt, 2.f * cim * dt);
  const uint32_t row = st + lane * 16;
  const int mi = lane >> 3;

  uint32_t af[4][4];
  {
    const float2 s8 = make_float2(w8.x, -w8.y), s16 = cmul(s8, s8);
    float2 v[8];
    v[0] = make_float2(c.x, -c.y);
    v[1] = cmul(v[0], s8);
#pragma unroll
    for (int i = 2; i < 8; i++) v[i] = cmul(v[i - 2], s16);
    sts_row(row, v);
    v[0] = cmul(v[6], s16);
    v[1] = cmul(v[7], s16);
#pragma unroll
    for (int i = 2; i < 8; i++) v[i] = cmul(v[i - 2], s16);
    sts_row(row + 1024, v);
    __syncwarp();
    const uint32_t a = st + (mi & 1) * 1024 + ((mi >> 1) * 8 + (lane & 7)) * 16;
#pragma unroll
    for (int ks = 0; ks < 4; ks++) ldsm4t(af[ks], a + (ks >> 1) * 512 + (ks & 1) * 256);
    __syncwarp();
  }
  float acc[5][4];
#pragma unroll
  for (int t = 0; t < 5; t++) acc[t][0] = acc[t][1] = acc[t][2] = acc[t][3] = 0.f;
  auto tile = [&](int t, uint32_t a) {
    uint32_t br[4], bi[4];
    ldsm4t(br, a);
    ldsm4t(bi, a + 512);
    mma_bf16(acc[t], af[0][0], af[0][1], af[0][2], af[0][3], br[0], br[1]);
    mma_bf16(acc[t], af[1][0], af[1][1], af[1][2], af[1][3], br[2], br[3]);
    mma_bf16(acc[t], af[2][0], af[2][1], af[2][2], af[2][3], bi[0], bi[1]);
    mma_bf16(acc[t], af[3][0], af[3][1], af[3][2], af[3][3], bi[2], bi[3]);
  };
  float2 h[8], v[8];
  h[0] = make_float2(1.f, 0.f);
  h[1] = w1;
  h[2] = cmul(w1, w1);
  h[3] = cmul(h[2], w1);
  h[4] = cmul(h[2], h[2]);
  h[5] = cmul(h[4], w1);
  h[6] = cmul(h[4], h[2]);
  h[7] = cmul(h[4], h[3]);
  sts_row(row, h);
  v[0] = w128;
#pragma unroll
  for (int i = 1; i < 8; i++) v[i] = cmul(w128, h[i]);
  sts_row(row + 1024, v);
  __syncwarp();
  tile(0, row);
  tile(1, row + 1024);
  __syncwarp();
  const float2 a2 = cmul(w128, w128), a3 = cmul(a2, w128);
  v[0] = a2; v[1] = cmul(a2, h[2]); v[2] = cmul(a2, h[4]); v[3] = cmul(a2, h[6]);
  v[4] = a3; v[5] = cmul(a3, h[2]); v[6] = cmul(a3, h[4]); v[7] = cmul(a3, h[6]);
  sts_row(row, v);
  v[0] = cmul(a2, a2); v[2] = cmul(a3, a2); v[4] = cmul(v[0], a2); v[6] = cmul(v[2], a2);
  v[1] = cmul(v[0], h[4]); v[3] = cmul(v[2], h[4]); v[5] = cmul(v[4], h[4]); v[7] = cmul(v[6], h[4]);
  sts_row(row + 1024, v);
  __syncwarp();
  tile(2, row);
  tile(3, row + 1024);
  __syncwarp();
  v[0] = cmul(v[4], a2);
  v[1] = cmul(v[6], a2);
#pragma unroll
  for (int i = 2; i < 8; i++) v[i] = cmul(v[i - 2], a2);
  sts_row(row, v);
  __syncwarp();
  tile(4, row);
  const float2 a16 = cmul(v[6], a2);
  float kl = fmaf(c.x, a16.x, -c.y * a16.y);
#pragma unroll
  for (int o = 16; o > 0; o >>= 1) kl += __shfl_xor_sync(0xffffffffu, kl, o);
  __syncwarp();
  const uint32_t o = st + ((lane >> 2) * 40 + 2 * (lane & 3)) * 4;
#pragma unroll
  for (int t = 0; t < 5; t++) {
    sts64(o + t * 32, __float_as_uint(acc[t][0]), __float_as_uint(acc[t][1]));
    sts64(o + t * 32 + 1280, __float_as_uint(acc[t][2]), __float_as_uint(acc[t][3]));
  }
  if (lane == 0) sts32(st + 2560, __float_as_uint(kl));
}

__device__ __forceinline__ uint32_t u_chunk(uint32_t ub, int w, int ci) {
  const int row = (ci >> 1) + 8;
  return ub + row * 128 + (((2 * w + (ci & 1)) ^ (row & 7)) << 4);
}

template <int J0>
__device__ __forceinline__ void conv_pass(uint32_t sb, int cta, int w, int lane PROF_PARAM) {
  const uint32_t bars = sb + kOffBar;
  const uint32_t ub = sb + kOffU, tb = sb + kOffTaps + w * 4096, vb = sb + kOffV + w * kVChan;
  const int mi = lane >> 3, n8 = lane & 7, r = lane >> 2, q = lane & 3;
  const uint32_t tx = r - 2 * q;
  float acc[8][4];
  {
    const float k512 = ldsf(tb + kTapK), k1024 = ldsf(tb + kTapK + 4);
#pragma unroll
    for (int e = 0; e < 4; e++) {
      const int t = 16 * (2 * q + (e & 1)) + r + 8 * (e >> 1);
      uint32_t a[4];
#pragma unroll
      for (int i = 0; i < 4; i++) a[i] = u_chunk(ub, w, (t - 1 - i) >> 3) + ((t - 1 - i) & 7) * 2;
#pragma unroll
      for (int j = J0; j < J0 + 8; j++) {
        float v = 0.f;
        if (j >= 4) v = k512 * (lds_bf16(a[0] + (j - 4) * 1024) + lds_bf16(a[1] + (j - 4) * 1024));
        if (j >= 8) v = fmaf(k1024, lds_bf16(a[2] + (j - 8) * 1024) + lds_bf16(a[3] + (j - 8) * 1024), v);
        acc[j - J0][e] = v;
      }
    }
  }
#pragma unroll
  for (int c = 0; c < 2; c++) {
    uint2 p[5];
#pragma unroll
    for (int h = 0; h < 5; h++)
      if (h + 4 < J0 + 8) p[h] = lds64(tb + (c ? kTapB : kTapA) + (tx + 8 + 8 * h) * 8);
    const uint32_t qa = vb + (mi >> 1) * kV5e + n8 * 16 +
                        (c ? ((mi & 1) ? kV3e : kV3o - 16) : ((mi & 1) ? kV3o : kV3e));
    if (J0 == 8 && c == 0) {
      if (threadIdx.x == 256) STAMP(13);
      bar_sync(NB_P1, 384);
      if (threadIdx.x == 256) STAMP(14);
    }
#pragma unroll
    for (int s = J0 + 3; s >= 0; s--) {
      uint32_t v[4];
      ldsm4t(v, qa + s * 128);
#pragma unroll
      for (int h = 0; h < 5; h++)
        if (s + h + 4 >= J0 && s + h + 4 < J0 + 8) mma_bf16(acc[s + h + 4 - J0], v[0], v[1], v[2], v[3], p[h].x, p[h].y);
    }
  }
  if (J0 == 8) {
    uint2 p[8];
#pragma unroll
    for (int h = 0; h < 8; h++) p[h] = lds64(tb + kTapC + (tx + 8 + 8 * h) * 8);
    const uint32_t qa = vb + kV7e + mi * 1024 + n8 * 16;
#pragma unroll
    for (int s = 0; s < 8; s++) {
      uint32_t v[4];
      ldsm4t(v, qa + s * 128);
#pragma unroll
      for (int h = 7; h >= 0; h--)
        if (s + h < 8) mma_bf16(acc[s + h], v[0], v[1], v[2], v[3], p[h].x, p[h].y);
    }
  }
  __syncwarp();
  if (lane < 2) mbar_arrive_cta(bars + B_RDYB * 8, lane);
  if (threadIdx.x == 256) STAMP(15);
  if (threadIdx.x == 128) STAMP(18);
  {
    const uint32_t ta = tb + (tx + 16) * 4;
#pragma unroll 1
    for (int rho = 0; rho < 8; rho++) {
      const int row = 8 * (mi >> 1) + 8 - rho + n8;
      const uint32_t ga = ub + row * 128 + (((2 * w + (mi & 1)) ^ (row & 7)) << 4);
      const uint32_t tr = ta + rho * 64;
      uint32_t T[4][3];
#pragma unroll
      for (int e = 0; e < 4; e++) {
        T[e][0] = lds32(tr + e * 512);
        T[e][1] = lds32(tr + e * 512 + 32);
        T[e][2] = lds32(tr + e * 512 - 32);
      }
#pragma unroll
      for (int s = J0 + 6; s >= (J0 ? J0 - 4 : 0); s -= 2) {
        uint32_t g[4];
        ldsm4(g, ga + s * 1024);
#pragma unroll
        for (int e = 0; e < 4; e++)
          if (s + 1 + e >= J0 && s + 1 + e < J0 + 8)
            mma_bf16(acc[s + 1 + e - J0], T[e][0], T[e][1], T[e][2], T[e][0], g[2], g[3]);
#pragma unroll
        for (int e = 0; e < 4; e++)
          if (s + e >= J0 && s + e < J0 + 8) mma_bf16(acc[s + e - J0], T[e][0], T[e][1], T[e][2], T[e][0], g[0], g[1]);
      }
    }
    const uint32_t t0 = lds32(ta + 2048), t1 = lds32(ta + 2048 + 32), t2 = lds32(ta + 2048 - 32);
    const uint32_t ga = ub + (8 * (mi >> 1) + 8 + n8) * 128 + (((2 * w + (mi & 1)) ^ n8) << 4);
#pragma unroll
    for (int s = J0 + 2; s >= (J0 ? J0 - 4 : 0); s -= 2) {
      uint32_t g[4];
      ldsm4(g, ga + s * 1024);
      mma_bf16(acc[s + 5 - J0], t0, t1, t2, t0, g[2], g[3]);
      mma_bf16(acc[s + 4 - J0], t0, t1, t2, t0, g[0], g[1]);
    }
  }
  {
    const int ch = (cta & 15) * 4 + w, ci = 2 * n8 + (mi & 1);
    const uint32_t a = tb + (J0 + (mi >> 1)) * 256 + ((ci ^ (ch & 7) ^ (ci >> 3)) << 4);
    uint32_t p[8][2];
#pragma unroll
    for (int j = 0; j < 8; j++) {
      p[j][0] = pack2(acc[j][0], acc[j][1]);
      p[j][1] = pack2(acc[j][2], acc[j][3]);
    }
    asm volatile("" ::"r"(p[0][0]), "r"(p[4][0]) : "memory");
    if (threadIdx.x == 256) STAMP(16);
    if (threadIdx.x == 128) STAMP(19);
    bar_sync(NB_CONV, 384);
#pragma unroll
    for (int j = 0; j < 8; j += 2) stsm4t(a + j * 256, p[j][0], p[j][1], p[j + 1][0], p[j + 1][1]);
    fence_async_smem();
    __syncwarp();
    if (lane < 8) {
      bulk_store(g_aT + (size_t)(((cta >> 4) * 16 + J0 + lane) * 64 + ch) * 256, tb + (J0 + lane) * 256, 256);
      bulk_commit();
      bulk_wait_read();
    }
    __syncwarp();
    if (lane < 2) mbar_arrive_cta(bars + B_RDYC * 8, lane);
    if (lane < 8) { bulk_wait(); fence_async_all(); }
    __syncwarp();
    if (lane == 0) { __threadfence(); cnt_add(C_A + (cta >> 4)); }
    if (threadIdx.x == 256) STAMP(17);
  }
}

__device__ __forceinline__ void issue_p1(uint32_t sb, int step, const CUtensorMap* mx, const CUtensorMap* mw,
                                         int ft, int tt, uint32_t rank) {
  const int slot = (step + 4) % 5;
  const uint32_t bar = sb + kOffBar + (B_FULL1 + slot) * 8, dst = sb + slot * kStage;
  mbar_expect(bar, kStage);
  tma2d_mc(dst + rank * 8192, mw, ft * 128, step * 32, bar);
  tma2d_mc(dst + rank * 8192 + 4096, mw, ft * 128 + 64, step * 32, bar);
  tma2d(dst + kStageX, mx, step * 32, tt * kTok1, bar);
}

__global__ void __launch_bounds__(kThreads, 1)
fused_kernel(const __grid_constant__ CUtensorMap map_x, const __grid_constant__ CUtensorMap map_wg,
             const __grid_constant__ CUtensorMap map_wu, const __grid_constant__ CUtensorMap map_wd,
             const __grid_constant__ CUtensorMap map_ut, const __grid_constant__ CUtensorMap map_out,
             const Params prm) {
  extern __shared__ __align__(1024) uint8_t smem[];
  const uint32_t sb = (uint32_t)__cvta_generic_to_shared(smem);
  const uint32_t bars = sb + kOffBar;
  const int tid = threadIdx.x, lane = tid & 31;
  const int warp = __shfl_sync(0xffffffffu, tid >> 5, 0);
  const int cta = blockIdx.x, cid = cta >> 1;
  const uint32_t rank = cta & 1;
  const int ft = cid % 11, tt = (cid / 11) * 2 + rank;
  const int tj = cid >> 2, dt = (cid & 3) * 2 + rank;
  const bool full_cta = cta < 128;

  float lar = 0.f, aim = 0.f, cre = 0.f, cim = 0.f, ldt = 0.f;
  if (full_cta) {
    const int i = cta * 512 + tid;
    lar = ldg_bf16(prm.log_a + i);
    aim = ldg_bf16(prm.a_im + i);
    cre = ldg_bf16(prm.c_re + i);
    cim = ldg_bf16(prm.c_im + i);
    ldt = ldg_bf16(prm.log_dt + cta * 4 + (warp >> 2));
  }
  if (warp == 12) {
    if (sb & 1023) __trap();
    for (int i = lane; i < B_COUNT; i += 32) {
      const uint32_t c = (i >= B_EMPTY1 && i < B_FULLW) ? 4
                         : ((i >= B_EMPTYH && i < B_XR) || i == B_RDYA) ? 2 : (i >= B_RDYB ? 16 : 1);
      mbar_init(bars + i * 8, c);
    }
    asm volatile("fence.mbarrier_init.release.cluster;" ::: "memory");
  }
  asm volatile("barrier.cluster.arrive.relaxed.aligned;" ::: "memory");
  asm volatile("barrier.cluster.wait.aligned;" ::: "memory");
  if (warp >= 12) {
    const CUtensorMap* mw = rank ? &map_wu : &map_wg;
    if (warp < 15) {
      if (lane == 0) {
        const int s0 = (warp - 12) * 2;
        issue_p1(sb, s0, &map_x, mw, ft, tt, rank);
        if (warp < 14) issue_p1(sb, s0 + 1, &map_x, mw, ft, tt, rank);
      }
    } else if (full_cta) {
      if (lane == 0) mbar_expect(bars + B_XR * 8, 16384);
      __syncwarp();
      if (lane < 16) bulk_load(sb + kOffU + lane * kXRow, prm.x + (cta * 16 + lane) * kD, 1024, bars + B_XR * 8);
    }
    __syncwarp();
  }
  if (tid == 0) STAMP(0);
  if (full_cta) kgen_task(sb + kOffV + warp * kPart, lane, lar, aim, cre, cim, ldt);
  if (tid == 0) STAMP(1);

  if (warp < 8) {
    bar_arrive(NB_KGEN, kThreads);
    asm volatile("setmaxnreg.inc.sync.aligned.u32 208;");
    const int wg = warp >> 2, wq = warp & 3;
    const bool leader = (tid & 127) == 0;
    const int mi = lane >> 3, n8 = lane & 7;
    if (tid == 0) STAMP(2);
    {
      float ag[88], au[88];
      int slot = 4;
      uint32_t par = 0;
#pragma unroll 1
      for (int step = 0; step < 16; step++) {
        mbar_wait(bars + (B_FULL1 + slot) * 8, par);
        const uint32_t st = sb + slot * kStage;
        const uint64_t dg = make_desc(st + wg * 4096, 1024, 1), dx = make_desc(st + kStageX, 512, 2);
        wg_fence();
        wgmma_n176(ag, dg, dx, step);
        wgmma_n176(au, dg + 512, dx, step);
        wgmma_n176(ag, dg + 128, dx + 2, 1);
        wgmma_n176(au, dg + 640, dx + 2, 1);
        wg_commit();
        wg_wait<1>();
        if (leader && step >= 1 && step <= 14) {
          const uint32_t e = bars + (B_EMPTY1 + (slot == 0 ? 4 : slot - 1)) * 8;
          mbar_arrive_cta(e, 0);
          mbar_arrive_cta(e, 1);
        }
        if (slot == 3) par ^= 1;
        slot = slot == 4 ? 0 : slot + 1;
      }
      wg_wait<0>();
      if (tid == 0) STAMP(3);
      bar_sync(NB_P1, 384);
      const uint32_t hs = sb + (3 + wg) * kStage;
      const uint32_t a = hs + ((mi >> 1) * 8 + n8) * 128 + (((2 * wq + (mi & 1)) ^ n8) << 4);
#pragma unroll
      for (int i = 0; i < 22; i += 2) {
        uint32_t p[4];
#pragma unroll
        for (int k = 0; k < 4; k++) {
          float h[2];
#pragma unroll
          for (int e = 0; e < 2; e++) {
            const float hg = 0.5f * ag[4 * i + 2 * k + e];
            float t; asm("tanh.approx.f32 %0, %1;" : "=f"(t) : "f"(hg));
            h[e] = fmaf(hg, t, hg) * au[4 * i + 2 * k + e];
          }
          p[k] = pack2(h[0], h[1]);
        }
        stsm4t(a + i * 1024, p[0], p[1], p[2], p[3]);
      }
      fence_async_smem();
      if (wg == 0) bar_arrive(NB_H, 160); else bar_arrive(NB_H + 1, 160);
      if (tid == 0) STAMP(4);
    }
    if (wg == 0) {
      if (full_cta) {
        float d[64];
        bar_sync(NB_CONV, 384);
        if (tid == 0) STAMP(6);
#pragma unroll
        for (int kt = 0; kt < kNumFt; kt++) {
          mbar_wait(bars + (B_FULLW + kt % kNW) * 8, (kt / kNW) & 1);
          mbar_wait(bars + (B_FULLH + kt % kNH) * 8, (kt / kNH) & 1);
          const uint64_t dw = make_desc(sb + wd_slot(kt % kNW), 1024, 1), dh = make_desc(sb + h_slot(kt % kNH), 1024, 1);
          wg_fence();
#pragma unroll
          for (int k = 0; k < (kt == kNumFt - 1 ? 2 : 4); k++) wgmma_n128(d, dw + k * 128, dh + k * 2, kt | k);
          wg_commit();
          if (kt >= 1) {
            wg_wait<1>();
            if (leader) {
              if (kt - 1 + kNW < kNumFt) mbar_arrive(bars + (B_EMPTYW + (kt - 1) % kNW) * 8);
              if (kt - 1 + kNH < kNumFt) {
                mbar_arrive_cta(bars + (B_EMPTYH + (kt - 1) % kNH) * 8, 0);
                mbar_arrive_cta(bars + (B_EMPTYH + (kt - 1) % kNH) * 8, 1);
              }
            }
          }
        }
        asm volatile("barrier.cluster.arrive.relaxed.aligned;" ::: "memory");
        mbar_wait(bars + B_A * 8, 0);
        wg_wait<0>();
        if (tid == 0) STAMP(7);
        const uint32_t aa = sb + kOffU + (16 * wq + 8 * (mi & 1) + n8) * 256 + (((mi >> 1) ^ n8) << 4);
        const uint32_t ga = sb + kOffGate + (lane & 3) * 16;
        const uint32_t oa = sb + ((mi >> 1) * 8 + n8) * 128 + (((2 * wq + (mi & 1)) ^ n8) << 4);
#pragma unroll
        for (int i = 0; i < 16; i += 2) {
          uint32_t av[4], p[4];
          ldsm4(av, aa ^ ((i ^ (i >> 3)) << 4));
#pragma unroll
          for (int b = 0; b < 2; b++) {
            const uint4 g = lds128(ga + (i + b) * 64);
#pragma unroll
            for (int hf = 0; hf < 2; hf++) {
              const uint32_t v = av[2 * b + hf];
              const float o0 = fmaf(__uint_as_float(g.x), bf_lo(v), __uint_as_float(g.y) * d[4 * (i + b) + 2 * hf]);
              const float o1 = fmaf(__uint_as_float(g.z), bf_hi(v), __uint_as_float(g.w) * d[4 * (i + b) + 2 * hf + 1]);
              p[2 * b + hf] = pack2(o0, o1);
            }
          }
          stsm4t(oa + i * 1024, p[0], p[1], p[2], p[3]);
        }
        fence_async_smem();
        bar_sync(NB_OUT, 128);
        if (leader) {
          tma2d_store(&map_out, sb, dt * 64, tj * 128);
          bulk_commit();
          bulk_wait_read();
          STAMP(8);
        }
        __syncwarp();
      } else {
        asm volatile("barrier.cluster.arrive.relaxed.aligned;" ::: "memory");
      }
      asm volatile("barrier.cluster.wait.aligned;" ::: "memory");
    } else if (full_cta) {
      mbar_wait(bars + B_U * 8, 0);
      conv_pass<0>(sb, cta, wq, lane PROF_ARG);
    }
  } else if (warp < 12) {
    asm volatile("setmaxnreg.dec.sync.aligned.u32 72;");
    if (!full_cta) {
      bar_arrive(NB_KGEN, kThreads);
      bar_arrive(NB_P1, 384);
      return;
    }
    const int w = warp - 8, mi = lane >> 3, n8 = lane & 7, r = lane >> 2, q = lane & 3;
    const uint32_t ub = sb + kOffU, tb = sb + kOffTaps + w * 4096, vb = sb + kOffV + w * kVChan;
    {
      const uint4 gw0 = __ldg(reinterpret_cast<const uint4*>(prm.gate_w) + lane);
      const uint4 gw1 = __ldg(reinterpret_cast<const uint4*>(prm.gate_w) + 32 + lane);
      mbar_wait(bars + B_XR * 8, 0);
      const int tok = (n8 >> 1) * 4 + (n8 & 1) + 2 * (mi & 1);
      const uint32_t a = ub + tok * kXRow + (w * 16 + (mi >> 1)) * 16;
      uint8_t* dst = g_uT + (size_t)cta * 16384 + (w * 128 + r) * 32 + q * 8;
#pragma unroll
      for (int c = 0; c < 16; c += 2) {
        uint32_t v[4];
        ldsm4t(v, a + c * 16);
        *reinterpret_cast<uint2*>(dst + c * 256) = make_uint2(v[0], v[1]);
        *reinterpret_cast<uint2*>(dst + c * 256 + 256) = make_uint2(v[2], v[3]);
      }
      float s[4];
#pragma unroll
      for (int t = 0; t < 4; t++) {
        const uint4 x0 = lds128(ub + (4 * w + t) * kXRow + lane * 16), x1 = lds128(ub + (4 * w + t) * kXRow + 512 + lane * 16);
        const uint32_t xv[8] = {x0.x, x0.y, x0.z, x0.w, x1.x, x1.y, x1.z, x1.w};
        const uint32_t gv[8] = {gw0.x, gw0.y, gw0.z, gw0.w, gw1.x, gw1.y, gw1.z, gw1.w};
        float acc = 0.f;
#pragma unroll
        for (int k = 0; k < 8; k++) {
          uint32_t m; asm("mul.rn.bf16x2 %0, %1, %2;" : "=r"(m) : "r"(xv[k]), "r"(gv[k]));
          acc += bf_lo(m) + bf_hi(m);
        }
        s[t] = acc;
      }
#pragma unroll
      for (int o = 16; o > 0; o >>= 1) {
#pragma unroll
        for (int t = 0; t < 4; t++) s[t] += __shfl_xor_sync(0xffffffffu, s[t], o);
      }
      if (lane < 4) {
        const float z = bf_round(lane == 0 ? s[0] : lane == 1 ? s[1] : lane == 2 ? s[2] : s[3]);
        const float g = bf_round(1.f / (1.f + expf(-z)));
        g_gate[cta * 16 + 4 * w + lane] = make_float2(g, bf_round(1.f - g));
      }
      fence_async_all();
      bar_sync(NB_WG2, 128);
      if (tid == 256) { __threadfence(); cnt_add(C_U); STAMP(10); }
    }
    {
      const float dsk = ldg_bf16(prm.d_skip + cta * 4 + w);
      bar_sync(NB_KGEN, kThreads);
#pragma unroll
      for (int i = 0; i < 5; i++) {
        const uint32_t a = vb + i * 512 + lane * 16;
        const uint4 p0 = lds128(a), p1 = lds128(a + kPart), p2 = lds128(a + 2 * kPart), p3 = lds128(a + 3 * kPart);
        sts128(a, __float_as_uint((__uint_as_float(p0.x) + __uint_as_float(p1.x)) + (__uint_as_float(p2.x) + __uint_as_float(p3.x))),
               __float_as_uint((__uint_as_float(p0.y) + __uint_as_float(p1.y)) + (__uint_as_float(p2.y) + __uint_as_float(p3.y))),
               __float_as_uint((__uint_as_float(p0.z) + __uint_as_float(p1.z)) + (__uint_as_float(p2.z) + __uint_as_float(p3.z))),
               __float_as_uint((__uint_as_float(p0.w) + __uint_as_float(p1.w)) + (__uint_as_float(p2.w) + __uint_as_float(p3.w))));
      }
      if (lane == 0)
        sts32(vb + 2560, __float_as_uint((ldsf(vb + 2560) + ldsf(vb + 2560 + kPart)) + (ldsf(vb + 2560 + 2 * kPart) + ldsf(vb + 2560 + 3 * kPart))));
      __syncwarp();
      auto near_tap = [&](int m) {
        const int d = min(max(m, 0), 512);
        const int p = (d >= 256 && (d & 1)) ? ((d + 1) & ~3) : d;
        const float v = ldsf(vb + k_index(p));
        return m == 0 ? v + dsk : (m == d ? v : 0.f);
      };
#pragma unroll 1
      for (int x = lane - 16; x < 528; x += 32) sts32(tb + (x + 16) * 4, pack2(near_tap(x), near_tap(x - 1)));
      auto far_tap = [&](int k, int k0, int off) {
        const int d = min(max(k, k0), 2 * k0 - 1);
        const float v = ldsf(vb + k_index(16 * d + off));
        return k == d ? v : 0.f;
      };
#pragma unroll 1
      for (int i = lane; i < 168; i += 32) {
        const int k0 = i < 96 ? 32 : 64;
        const int x = i < 48 ? i + 24 : (i < 96 ? i - 24 : i - 40);
        const int o0 = i < 48 ? 4 : (i < 96 ? 12 : 8), o1 = i < 48 ? 8 : 16;
        sts64(tb + kTapA + i * 8, pack2(far_tap(x, k0, o0), far_tap(x - 1, k0, o0)),
              pack2(far_tap(x, k0, o1), far_tap(x - 1, k0, o1)));
      }
      if (lane < 2) sts32(tb + kTapK + lane * 4, lds32(vb + k_index(512 << lane)));
      __syncwarp();
      if (tid == 256) STAMP(11);
    }
    mbar_wait(bars + B_U * 8, 0);
    if (tid == 256) STAMP(12);
    {
      if (lane < 2) sts128(vb + (lane ? kV5o : kV3o) - 16, 0u, 0u, 0u, 0u);
      const uint32_t a0 = u_chunk(ub, w, lane - 3), a1 = u_chunk(ub, w, lane - 2);
      const uint32_t a2 = u_chunk(ub, w, lane - 1), a3 = u_chunk(ub, w, lane);
      const uint32_t o35 = vb + (lane >> 1) * 16 + ((lane & 1) ? kV3o : kV3e);
      const uint32_t o79 = vb + (lane >> 1) * 16 + ((lane & 1) ? kV7o : kV7e);
#pragma unroll 1
      for (int it = 0; it < 6; it++) {
        const uint2 c0 = lds64(a0 + it * 2048 + 8);
        const uint4 c1 = lds128(a1 + it * 2048), c2 = lds128(a2 + it * 2048), c3 = lds128(a3 + it * 2048);
        const uint32_t e[13] = {c0.x, c0.y, c1.x, c1.y, c1.z, c1.w, c2.x, c2.y, c2.z, c2.w, c3.x, c3.y, c3.z};
        float S[26];
        S[0] = 0.f;
#pragma unroll
        for (int j = 0; j < 25; j++) S[j + 1] = S[j] + ((j & 1) ? bf_hi(e[j >> 1]) : bf_lo(e[j >> 1]));
        auto win = [&](uint32_t a, int hi, int lo) {
          sts128(a, pack2(S[hi] - S[lo], S[hi + 1] - S[lo + 1]), pack2(S[hi + 2] - S[lo + 2], S[hi + 3] - S[lo + 3]),
                 pack2(S[hi + 4] - S[lo + 4], S[hi + 5] - S[lo + 5]), pack2(S[hi + 6] - S[lo + 6], S[hi + 7] - S[lo + 7]));
        };
        win(o35 + it * 256, 18, 15);
        win(o35 + it * 256 + kV5e, 15, 10);
        if (it < 4) {
          win(o79 + it * 256, 16, 9);
          win(o79 + it * 256 + (kV9e - kV7e), 9, 0);
        }
      }
    }
    __syncwarp();
    conv_pass<8>(sb, cta, w, lane PROF_ARG);
  } else {
    bar_arrive(NB_KGEN, kThreads);
    asm volatile("setmaxnreg.dec.sync.aligned.u32 24;");
    if (warp == 13) {
      const uint32_t bytes = (tt == 11 ? kL - 11 * kTok1 : kTok1) * 128;
      uint8_t* dst = g_H + ((size_t)(2 * ft) * kL + tt * kTok1) * 128;
      bar_sync(NB_H, 160);
      if (lane == 0) bulk_store(dst, sb + 3 * kStage, bytes);
      bar_sync(NB_H + 1, 160);
      if (lane == 0) {
        bulk_store(dst + kL * 128, sb + 4 * kStage, bytes);
        bulk_commit();
        bulk_wait_read();
        mbar_arrive_cta(bars + B_RDYA * 8, 0);
        mbar_arrive_cta(bars + B_RDYA * 8, 1);
        bulk_wait();
        fence_async_all();
        cnt_add(C_H + tt);
        STAMP(5);
      }
    } else if (lane == 0) {
      if (warp == 12) {
        const CUtensorMap* mw = rank ? &map_wu : &map_wg;
#pragma unroll 1
        for (int step = 5; step < 16; step++) {
          mbar_wait(bars + (B_EMPTY1 + (step + 4) % 5) * 8, (step / 5 - 1) & 1);
          issue_p1(sb, step, &map_x, mw, ft, tt, rank);
        }
        if (full_cta) {
#pragma unroll 1
          for (int kt = 0; kt < kNumFt; kt++) {
            const int s = kt < kNW ? kt : kt - kNW;
            if (kt == 2 || kt == 5 || kt == 8) mbar_wait(bars + (B_EMPTY1 + (kt - 2) / 3) * 8, 0);
            if (kt == 12) mbar_wait(bars + B_RDYB * 8, 0);
            if (kt >= kNW) mbar_wait(bars + (B_EMPTYW + s) * 8, 0);
            mbar_expect(bars + (B_FULLW + s) * 8, 8192);
            tma2d(sb + wd_slot(s), &map_wd, dt * 64, kt * 64, bars + (B_FULLW + s) * 8);
          }
        }
      } else if (warp == 14) {
        if (full_cta) {
          const int t0 = tj * 128 + rank * 64;
          mbar_wait(bars + B_RDYB * 8, 0);
          cnt_wait(C_H + t0 / kTok1, 11);
          cnt_wait(C_H + (t0 + 63) / kTok1, 11);
          fence_async_all();
          STAMP(20);
          int s = 0;
          uint32_t par = 1;
#pragma unroll 1
          for (int kt = 0; kt < kNumFt; kt++) {
            if (kt == 2) mbar_wait(bars + B_RDYA * 8, 0);
            if (kt == 5) mbar_wait(bars + B_RDYC * 8, 0);
            if (kt >= kNH) mbar_wait(bars + (B_EMPTYH + s) * 8, par);
            mbar_expect(bars + (B_FULLH + s) * 8, 16384);
            bulk_load_mc(sb + h_slot(s) + rank * 8192, g_H + ((size_t)kt * kL + t0) * 128, 8192, bars + (B_FULLH + s) * 8);
            if (++s == kNH) { s = 0; par ^= 1; }
          }
          cnt_done();
        }
      } else if (warp == 15) {
        if (full_cta) {
          cnt_wait(C_U, 128);
          fence_async_all();
          STAMP(21);
          mbar_expect(bars + B_U * 8, 17408);
          tma2d(sb + kOffU, &map_ut, cta * 64, -8, bars + B_U * 8);
          mbar_expect(bars + B_A * 8, 17408);
          bulk_load(sb + kOffGate, g_gate + tj * 128, 1024, bars + B_A * 8);
          mbar_wait(bars + B_RDYC * 8, 0);
          cnt_wait(C_A + dt, 128);
          fence_async_all();
          STAMP(22);
          bulk_load(sb + kOffU, g_aT + (size_t)(dt * 16 + tj) * 16384, 16384, bars + B_A * 8);
          cnt_done();
        }
      }
    }
  }
}

typedef CUresult (*EncodeFn)(CUtensorMap*, CUtensorMapDataType, cuuint32_t, void*, const cuuint64_t*, const cuuint64_t*,
                             const cuuint32_t*, const cuuint32_t*, CUtensorMapInterleave, CUtensorMapSwizzle,
                             CUtensorMapL2promotion, CUtensorMapFloatOOBfill);

void make_map(EncodeFn enc, CUtensorMap* m, const void* base, uint64_t cols, uint64_t rows, uint32_t bc, uint32_t br,
              CUtensorMapSwizzle sw) {
  const cuuint64_t dims[2] = {cols, rows}, strides[1] = {cols * 2};
  const cuuint32_t box[2] = {bc, br}, es[2] = {1, 1};
  enc(m, CU_TENSOR_MAP_DATA_TYPE_BFLOAT16, 2, const_cast<void*>(base), dims, strides, box, es,
      CU_TENSOR_MAP_INTERLEAVE_NONE, sw, CU_TENSOR_MAP_L2_PROMOTION_L2_128B, CU_TENSOR_MAP_FLOAT_OOB_FILL_NONE);
}

}

extern "C" void kernel_launch(void* const* d_in, const int* in_sizes, int n_in, void* d_out, int out_size) {
  (void)in_sizes; (void)n_in; (void)out_size;
  static EncodeFn enc = nullptr;
  static void* ut = nullptr;
  if (!enc) {
    cudaDriverEntryPointQueryResult qr;
    cudaGetDriverEntryPoint("cuTensorMapEncodeTiled", (void**)&enc, cudaEnableDefault, &qr);
    cudaGetSymbolAddress(&ut, g_uT);
    cudaFuncSetAttribute(fused_kernel, cudaFuncAttributeMaxDynamicSharedMemorySize, kSmemBytes);
  }
  CUtensorMap mx, mg, mu, md, mt, mo;
  make_map(enc, &mx, d_in[0], kD, kL, 32, kTok1, CU_TENSOR_MAP_SWIZZLE_64B);
  make_map(enc, &mg, d_in[8], kF, kD, 64, 32, CU_TENSOR_MAP_SWIZZLE_128B);
  make_map(enc, &mu, d_in[9], kF, kD, 64, 32, CU_TENSOR_MAP_SWIZZLE_128B);
  make_map(enc, &md, d_in[10], kD, kF, 64, 64, CU_TENSOR_MAP_SWIZZLE_128B);
  make_map(enc, &mt, ut, 8192, 128, 64, 136, CU_TENSOR_MAP_SWIZZLE_128B);
  make_map(enc, &mo, d_out, kD, kL, 64, 128, CU_TENSOR_MAP_SWIZZLE_128B);
  Params p;
  p.x = (const __nv_bfloat16*)d_in[0];
  p.log_a = (const __nv_bfloat16*)d_in[1];
  p.a_im = (const __nv_bfloat16*)d_in[2];
  p.c_re = (const __nv_bfloat16*)d_in[3];
  p.c_im = (const __nv_bfloat16*)d_in[4];
  p.log_dt = (const __nv_bfloat16*)d_in[5];
  p.d_skip = (const __nv_bfloat16*)d_in[6];
  p.gate_w = (const __nv_bfloat16*)d_in[11];

  cudaLaunchConfig_t cfg = {};
  cfg.gridDim = dim3(132);
  cfg.blockDim = dim3(kThreads);
  cfg.dynamicSmemBytes = kSmemBytes;
  cfg.stream = cudaStreamPerThread;
  cudaLaunchAttribute at[1];
  at[0].id = cudaLaunchAttributeClusterDimension;
  at[0].val.clusterDim.x = 2;
  at[0].val.clusterDim.y = 1;
  at[0].val.clusterDim.z = 1;
  cfg.attrs = at;
  cfg.numAttrs = 1;
  cudaLaunchKernelEx(&cfg, fused_kernel, mx, mg, mu, md, mt, mo, p);
}
```

```cpp
#include <cuda_runtime.h>
#include <cuda_bf16.h>
#include <cuda.h>
#include <stdint.h>

namespace {

constexpr int kL = 2048, kD = 512, kF = 1376;
constexpr int kTok1 = 176;
constexpr int kNumFt = 22;
constexpr int kThreads = 512;
constexpr int kRegW = 6;
constexpr int kEarly = 6;
constexpr int kSkew = 11;

constexpr uint32_t kS = 1024, kUnit = 8192, kStageX = 11264, kStageBytes = 2 * kUnit + kStageX;
constexpr uint32_t kOffW1 = 5 * kUnit, kOffX = 10 * kUnit, kOffI = 17 * kUnit;
constexpr uint32_t kOffV = 19 * kUnit, kOffTaps = 24 * kUnit, kOffU = 26 * kUnit, kOffGate = 230400;
constexpr uint32_t kOffBar = 231424, kOffKl = kOffBar + 512, kOffZero = kOffKl + 64, kSmemBytes = 232448;
constexpr uint32_t kOffHs = 2 * kUnit;
constexpr uint32_t kVChan = 10240, kPart = 2560, kIChan = 3072;
constexpr uint32_t kV3e = 0, kV3o = 1536, kV5e = 3072, kV7e = 6144, kV9e = 8192;
constexpr uint32_t kTapA = 2176, kTapB = kTapA + 384, kTapC = kTapB + 384;

constexpr int B_FULL1 = 0, B_EMPTY1 = 5, B_XR = 10, B_U = 11, B_P1 = 12, B_RDYI = 13, B_RDYB = 14, B_RDYD = 15;
constexpr int B_A = 16, B_RDYA0 = 17, B_RDYA1 = 18, B_W1 = 19, B_H0 = 20, B_FULL2 = 21, B_CONS = 43, kNumCons = 15;
constexpr int B_SKEW = B_CONS + kNumCons, B_WR = B_SKEW + 1, B_WRD = B_WR + 1, B_F0 = B_WRD + 1;
constexpr int B_AP = B_F0 + 1, B_G = B_AP + 1, B_COUNT = B_G + 1;
constexpr unsigned long long kBarCounts = 0x8841114444411111ull;
constexpr int NB_GATE = 0, NB_CONV = 1, NB_PREP = 2, NB_H = 3, NB_OUT = 11, NB_WG2 = 12, NB_AST = 14, NB_KGEN = 15;
constexpr int C_U = 0, C_H = 1, C_A = 3, C_DONE = 11, C_COUNT = 12;

constexpr uint32_t kSched[kNumFt] = {
    0x4ca23a80u, 0xfcc3fec1u, 0x14004465u, 0xfd44f006u, 0x1821fcaau, 0xfd65fd4bu, 0x1d86ae8cu, 0xfda7b2cdu,
    0x21c8b46eu, 0x31e9b80fu, 0xfe0abcb0u, 0x48edc151u, 0xfd0ec692u, 0xfd2fc987u, 0x362bfec8u, 0xfe4cd009u,
    0xf450fdc2u, 0x3a71d4b3u, 0x3f12d958u, 0xff33de19u, 0xff54e29au, 0xff75e59bu};
constexpr uint32_t kOffOut = 5 * kUnit, kOffA = 3 * kUnit;
constexpr int kBarA = B_CONS + 8;
__host__ __device__ constexpr int p2_tile(int k) { return k < 10 ? 2 * k + 1 : k < 21 ? 2 * (k - 10) : k; }

__device__ __align__(1024) uint8_t g_H[kNumFt * kL * 128];
__device__ __align__(1024) uint8_t g_uT[128 * kD * 32];
__device__ __align__(1024) uint8_t g_aT[kD * kL * 2];
__device__ __align__(1024) uint16_t g_gate[kL];
__device__ unsigned long long g_cnt[C_COUNT * 16];

__device__ __forceinline__ bool elect() {
  uint32_t p;
  asm volatile("{\n.reg .pred P;\nelect.sync _|P, 0xffffffff;\nselp.u32 %0, 1, 0, P;\n}" : "=r"(p));
  return p;
}
__device__ __forceinline__ void mbar_init(uint32_t b, uint32_t c) {
  asm volatile("mbarrier.init.shared::cta.b64 [%0], %1;" ::"r"(b), "r"(c) : "memory");
}
__device__ __forceinline__ void mbar_expect(uint32_t b, uint32_t tx) {
  asm volatile("mbarrier.arrive.expect_tx.shared::cta.b64 _, [%0], %1;" ::"r"(b), "r"(tx) : "memory");
}
__device__ __forceinline__ void mbar_arrive(uint32_t b) {
  asm volatile("mbarrier.arrive.shared::cta.b64 _, [%0];" ::"r"(b) : "memory");
}
__device__ __forceinline__ void mbar_arrive_cta(uint32_t b, uint32_t cta) {
  asm volatile("{\n.reg .b32 r;\nmapa.shared::cluster.u32 r, %0, %1;\n"
               "mbarrier.arrive.shared::cluster.b64 _, [r];\n}" ::"r"(b), "r"(cta) : "memory");
}
__device__ __forceinline__ void mbar_arrive_mapped(uint32_t b) {
  asm volatile("mbarrier.arrive.shared::cluster.b64 _, [%0];" ::"r"(b) : "memory");
}
__device__ __forceinline__ void mbar_arrive_pair(uint32_t b) {
  mbar_arrive_cta(b, 0);
  mbar_arrive_cta(b, 1);
}
__device__ __forceinline__ void mbar_wait(uint32_t b, uint32_t parity) {
  asm volatile("{\n.reg .pred p;\n.reg .u32 n;\nmov.u32 n, 0;\n"
               "W_LOOP:\n"
               "mbarrier.try_wait.parity.shared::cta.b64 p, [%0], %1;\n"
               "@p bra W_DONE;\n"
               "add.u32 n, n, 1;\nsetp.lt.u32 p, n, 1000000;\n@p bra W_LOOP;\ntrap;\n"
               "W_DONE:\n}" ::"r"(b), "r"(parity) : "memory");
}
__device__ __forceinline__ uint32_t mbar_test(uint32_t b, uint32_t parity) {
  uint32_t ok;
  asm volatile("{\n.reg .pred p;\nmbarrier.test_wait.parity.shared::cta.b64 p, [%1], %2;\nselp.u32 %0, 1, 0, p;\n}"
               : "=r"(ok) : "r"(b), "r"(parity) : "memory");
  return ok;
}
__device__ __forceinline__ void sched_fence() {
  asm volatile("{\n.reg .pred p;\n.reg .u32 t;\nF_LOOP:\nmov.u32 t, %%clock;\nsetp.eq.u32 p, t, %0;\n@p bra F_LOOP;\n}"
               ::"n"(0) : "memory");
}
__device__ __forceinline__ void bar_arrive_pinned(int id, int n) {
  asm volatile("{\n.reg .pred p;\n.reg .u64 t;\nF_LOOP:\nbar.arrive %0, %1;\nmov.u64 t, %%clock64;\n"
               "setp.eq.u64 p, t, 0;\n@p bra F_LOOP;\n}" ::"r"(id), "r"(n) : "memory");
}
__device__ __forceinline__ void bar_sync(int id, int n) { asm volatile("bar.sync %0, %1;" ::"r"(id), "r"(n) : "memory"); }
__device__ __forceinline__ void bar_arrive(int id, int n) { asm volatile("bar.arrive %0, %1;" ::"r"(id), "r"(n) : "memory"); }
__device__ __forceinline__ void fence_async_smem() { asm volatile("fence.proxy.async.shared::cta;" ::: "memory"); }
__device__ __forceinline__ void fence_async_gmem() { asm volatile("fence.proxy.async.global;" ::: "memory"); }
__device__ __forceinline__ void cnt_add(int c, unsigned long long v) {
  asm volatile("red.release.gpu.global.add.u64 [%0], %1;" ::"l"(&g_cnt[c * 16]), "l"(v) : "memory");
}
__device__ __forceinline__ void cnt_wait(int c, unsigned long long mask, unsigned long long target) {
  unsigned long long v;
  unsigned n = 0;
  do {
    asm volatile("ld.acquire.gpu.global.u64 %0, [%1];" : "=l"(v) : "l"(&g_cnt[c * 16]) : "memory");
    if (++n > 4000000u) __trap();
  } while ((v & mask) != target);
  fence_async_gmem();
}
__device__ __forceinline__ void cnt_done() {
  if (atomicAdd(&g_cnt[C_DONE * 16], 1ull) == 127ull) {
#pragma unroll 1
    for (int i = 0; i < C_COUNT; i++) g_cnt[i * 16] = 0ull;
  }
}
__device__ __forceinline__ void tma2d(uint32_t dst, const CUtensorMap* m, int c0, int c1, uint32_t bar) {
  asm volatile("cp.async.bulk.tensor.2d.shared::cluster.global.mbarrier::complete_tx::bytes [%0], [%1, {%3, %4}], [%2];"
               ::"r"(dst), "l"(m), "r"(bar), "r"(c0), "r"(c1) : "memory");
}
__device__ __forceinline__ void tma3d(uint32_t dst, const CUtensorMap* m, int c0, int c1, int c2, uint32_t bar) {
  asm volatile("cp.async.bulk.tensor.3d.shared::cluster.global.mbarrier::complete_tx::bytes [%0], [%1, {%3, %4, %5}], [%2];"
               ::"r"(dst), "l"(m), "r"(bar), "r"(c0), "r"(c1), "r"(c2) : "memory");
}
__device__ __forceinline__ void tma2d_mc(uint32_t dst, const CUtensorMap* m, int c0, int c1, uint32_t bar) {
  asm volatile("cp.async.bulk.tensor.2d.shared::cluster.global.mbarrier::complete_tx::bytes.multicast::cluster"
               " [%0], [%1, {%3, %4}], [%2], %5;"
               ::"r"(dst), "l"(m), "r"(bar), "r"(c0), "r"(c1), "h"((uint16_t)3) : "memory");
}
__device__ __forceinline__ void tma2d_store(const CUtensorMap* m, uint32_t src, int c0, int c1) {
  asm volatile("cp.async.bulk.tensor.2d.global.shared::cta.bulk_group [%0, {%2, %3}], [%1];"
               ::"l"(m), "r"(src), "r"(c0), "r"(c1) : "memory");
}
__device__ __forceinline__ void bulk_load(uint32_t dst, const void* src, uint32_t bytes, uint32_t bar) {
  asm volatile("cp.async.bulk.shared::cluster.global.mbarrier::complete_tx::bytes [%0], [%1], %2, [%3];"
               ::"r"(dst), "l"(src), "r"(bytes), "r"(bar) : "memory");
}
__device__ __forceinline__ void bulk_load_mc(uint32_t dst, const void* src, uint32_t bytes, uint32_t bar) {
  asm volatile("cp.async.bulk.shared::cluster.global.mbarrier::complete_tx::bytes.multicast::cluster [%0], [%1], %2, [%3], %4;"
               ::"r"(dst), "l"(src), "r"(bytes), "r"(bar), "h"((uint16_t)3) : "memory");
}
__device__ __forceinline__ void bulk_store(void* dst, uint32_t src, uint32_t bytes) {
  asm volatile("cp.async.bulk.global.shared::cta.bulk_group [%0], [%1], %2;" ::"l"(dst), "r"(src), "r"(bytes) : "memory");
}
__device__ __forceinline__ void bulk_commit() { asm volatile("cp.async.bulk.commit_group;" ::: "memory"); }
__device__ __forceinline__ void bulk_wait_read() { asm volatile("cp.async.bulk.wait_group.read 0;" ::: "memory"); }
__device__ __forceinline__ void bulk_wait() { asm volatile("cp.async.bulk.wait_group 0;" ::: "memory"); }

__device__ __forceinline__ void wg_fence() { asm volatile("wgmma.fence.sync.aligned;" ::: "memory"); }
__device__ __forceinline__ void wg_commit() { asm volatile("wgmma.commit_group.sync.aligned;" ::: "memory"); }
template <int N> __device__ __forceinline__ void wg_wait() { asm volatile("wgmma.wait_group.sync.aligned %0;" ::"n"(N) : "memory"); }
__device__ __forceinline__ uint64_t make_desc(uint32_t off, uint32_t sbo, uint32_t swizzle) {
  return (uint64_t)(((kS + off) >> 4) | (1u << 16)) | ((uint64_t)((sbo >> 4) | (swizzle << 30)) << 32);
}

__device__ __forceinline__ void wgmma_n176(float (&d)[88], uint64_t da, uint64_t db, int acc) {
  asm volatile(
      "{\n.reg .pred p;\nsetp.ne.b32 p, %90, 0;\n"
      "wgmma.mma_async.sync.aligned.m64n176k16.f32.bf16.bf16 {"
      "%0,%1,%2,%3,%4,%5,%6,%7,%8,%9,%10,%11,%12,%13,%14,%15,"
      "%16,%17,%18,%19,%20,%21,%22,%23,%24,%25,%26,%27,%28,%29,%30,%31,"
      "%32,%33,%34,%35,%36,%37,%38,%39,%40,%41,%42,%43,%44,%45,%46,%47,"
      "%48,%49,%50,%51,%52,%53,%54,%55,%56,%57,%58,%59,%60,%61,%62,%63,"
      "%64,%65,%66,%67,%68,%69,%70,%71,%72,%73,%74,%75,%76,%77,%78,%79,"
      "%80,%81,%82,%83,%84,%85,%86,%87"
      "}, %88, %89, p, 1, 1, 1, 0;\n}\n"
      : "+f"(d[0]), "+f"(d[1]), "+f"(d[2]), "+f"(d[3]), "+f"(d[4]), "+f"(d[5]), "+f"(d[6]), "+f"(d[7]),
        "+f"(d[8]), "+f"(d[9]), "+f"(d[10]), "+f"(d[11]), "+f"(d[12]), "+f"(d[13]), "+f"(d[14]), "+f"(d[15]),
        "+f"(d[16]), "+f"(d[17]), "+f"(d[18]), "+f"(d[19]), "+f"(d[20]), "+f"(d[21]), "+f"(d[22]), "+f"(d[23]),
        "+f"(d[24]), "+f"(d[25]), "+f"(d[26]), "+f"(d[27]), "+f"(d[28]), "+f"(d[29]), "+f"(d[30]), "+f"(d[31]),
        "+f"(d[32]), "+f"(d[33]), "+f"(d[34]), "+f"(d[35]), "+f"(d[36]), "+f"(d[37]), "+f"(d[38]), "+f"(d[39]),
        "+f"(d[40]), "+f"(d[41]), "+f"(d[42]), "+f"(d[43]), "+f"(d[44]), "+f"(d[45]), "+f"(d[46]), "+f"(d[47]),
        "+f"(d[48]), "+f"(d[49]), "+f"(d[50]), "+f"(d[51]), "+f"(d[52]), "+f"(d[53]), "+f"(d[54]), "+f"(d[55]),
        "+f"(d[56]), "+f"(d[57]), "+f"(d[58]), "+f"(d[59]), "+f"(d[60]), "+f"(d[61]), "+f"(d[62]), "+f"(d[63]),
        "+f"(d[64]), "+f"(d[65]), "+f"(d[66]), "+f"(d[67]), "+f"(d[68]), "+f"(d[69]), "+f"(d[70]), "+f"(d[71]),
        "+f"(d[72]), "+f"(d[73]), "+f"(d[74]), "+f"(d[75]), "+f"(d[76]), "+f"(d[77]), "+f"(d[78]), "+f"(d[79]),
        "+f"(d[80]), "+f"(d[81]), "+f"(d[82]), "+f"(d[83]), "+f"(d[84]), "+f"(d[85]), "+f"(d[86]), "+f"(d[87])
      : "l"(da), "l"(db), "r"(acc));
}

__device__ __forceinline__ void wgmma_n128(float (&d)[64], uint64_t da, uint64_t db, int acc) {
  asm volatile(
      "{\n.reg .pred p;\nsetp.ne.b32 p, %66, 0;\n"
      "wgmma.mma_async.sync.aligned.m64n128k16.f32.bf16.bf16 {"
      "%0,%1,%2,%3,%4,%5,%6,%7,%8,%9,%10,%11,%12,%13,%14,%15,"
      "%16,%17,%18,%19,%20,%21,%22,%23,%24,%25,%26,%27,%28,%29,%30,%31,"
      "%32,%33,%34,%35,%36,%37,%38,%39,%40,%41,%42,%43,%44,%45,%46,%47,"
      "%48,%49,%50,%51,%52,%53,%54,%55,%56,%57,%58,%59,%60,%61,%62,%63"
      "}, %64, %65, p, 1, 1, 1, 0;\n}\n"
      : "+f"(d[0]), "+f"(d[1]), "+f"(d[2]), "+f"(d[3]), "+f"(d[4]), "+f"(d[5]), "+f"(d[6]), "+f"(d[7]),
        "+f"(d[8]), "+f"(d[9]), "+f"(d[10]), "+f"(d[11]), "+f"(d[12]), "+f"(d[13]), "+f"(d[14]), "+f"(d[15]),
        "+f"(d[16]), "+f"(d[17]), "+f"(d[18]), "+f"(d[19]), "+f"(d[20]), "+f"(d[21]), "+f"(d[22]), "+f"(d[23]),
        "+f"(d[24]), "+f"(d[25]), "+f"(d[26]), "+f"(d[27]), "+f"(d[28]), "+f"(d[29]), "+f"(d[30]), "+f"(d[31]),
        "+f"(d[32]), "+f"(d[33]), "+f"(d[34]), "+f"(d[35]), "+f"(d[36]), "+f"(d[37]), "+f"(d[38]), "+f"(d[39]),
        "+f"(d[40]), "+f"(d[41]), "+f"(d[42]), "+f"(d[43]), "+f"(d[44]), "+f"(d[45]), "+f"(d[46]), "+f"(d[47]),
        "+f"(d[48]), "+f"(d[49]), "+f"(d[50]), "+f"(d[51]), "+f"(d[52]), "+f"(d[53]), "+f"(d[54]), "+f"(d[55]),
        "+f"(d[56]), "+f"(d[57]), "+f"(d[58]), "+f"(d[59]), "+f"(d[60]), "+f"(d[61]), "+f"(d[62]), "+f"(d[63])
      : "l"(da), "l"(db), "r"(acc));
}

__device__ __forceinline__ void wgmma_n128_rs(float (&d)[64], const uint32_t (&a)[4], uint64_t db, int acc) {
  asm volatile(
      "{\n.reg .pred p;\nsetp.ne.b32 p, %69, 0;\n"
      "wgmma.mma_async.sync.aligned.m64n128k16.f32.bf16.bf16 {"
      "%0,%1,%2,%3,%4,%5,%6,%7,%8,%9,%10,%11,%12,%13,%14,%15,"
      "%16,%17,%18,%19,%20,%21,%22,%23,%24,%25,%26,%27,%28,%29,%30,%31,"
      "%32,%33,%34,%35,%36,%37,%38,%39,%40,%41,%42,%43,%44,%45,%46,%47,"
      "%48,%49,%50,%51,%52,%53,%54,%55,%56,%57,%58,%59,%60,%61,%62,%63"
      "}, {%64,%65,%66,%67}, %68, p, 1, 1, 0;\n}\n"
      : "+f"(d[0]), "+f"(d[1]), "+f"(d[2]), "+f"(d[3]), "+f"(d[4]), "+f"(d[5]), "+f"(d[6]), "+f"(d[7]),
        "+f"(d[8]), "+f"(d[9]), "+f"(d[10]), "+f"(d[11]), "+f"(d[12]), "+f"(d[13]), "+f"(d[14]), "+f"(d[15]),
        "+f"(d[16]), "+f"(d[17]), "+f"(d[18]), "+f"(d[19]), "+f"(d[20]), "+f"(d[21]), "+f"(d[22]), "+f"(d[23]),
        "+f"(d[24]), "+f"(d[25]), "+f"(d[26]), "+f"(d[27]), "+f"(d[28]), "+f"(d[29]), "+f"(d[30]), "+f"(d[31]),
        "+f"(d[32]), "+f"(d[33]), "+f"(d[34]), "+f"(d[35]), "+f"(d[36]), "+f"(d[37]), "+f"(d[38]), "+f"(d[39]),
        "+f"(d[40]), "+f"(d[41]), "+f"(d[42]), "+f"(d[43]), "+f"(d[44]), "+f"(d[45]), "+f"(d[46]), "+f"(d[47]),
        "+f"(d[48]), "+f"(d[49]), "+f"(d[50]), "+f"(d[51]), "+f"(d[52]), "+f"(d[53]), "+f"(d[54]), "+f"(d[55]),
        "+f"(d[56]), "+f"(d[57]), "+f"(d[58]), "+f"(d[59]), "+f"(d[60]), "+f"(d[61]), "+f"(d[62]), "+f"(d[63])
      : "r"(a[0]), "r"(a[1]), "r"(a[2]), "r"(a[3]), "l"(db), "r"(acc));
}

__device__ __forceinline__ void mma_bf16(float (&c)[4], uint32_t a0, uint32_t a1, uint32_t a2, uint32_t a3,
                                         uint32_t b0, uint32_t b1) {
  asm volatile("mma.sync.aligned.m16n8k16.row.col.f32.bf16.bf16.f32 {%0,%1,%2,%3}, {%4,%5,%6,%7}, {%8,%9}, {%0,%1,%2,%3};"
               : "+f"(c[0]), "+f"(c[1]), "+f"(c[2]), "+f"(c[3])
               : "r"(a0), "r"(a1), "r"(a2), "r"(a3), "r"(b0), "r"(b1));
}
__device__ __forceinline__ void mma_f16(float (&c)[4], uint32_t a0, uint32_t a1, uint32_t a2, uint32_t a3,
                                        uint32_t b0, uint32_t b1) {
  asm volatile("mma.sync.aligned.m16n8k16.row.col.f32.f16.f16.f32 {%0,%1,%2,%3}, {%4,%5,%6,%7}, {%8,%9}, {%0,%1,%2,%3};"
               : "+f"(c[0]), "+f"(c[1]), "+f"(c[2]), "+f"(c[3])
               : "r"(a0), "r"(a1), "r"(a2), "r"(a3), "r"(b0), "r"(b1));
}
__device__ __forceinline__ void ldsm4(uint32_t (&r)[4], uint32_t a) {
  asm volatile("ldmatrix.sync.aligned.m8n8.x4.shared.b16 {%0,%1,%2,%3}, [%4];"
               : "=r"(r[0]), "=r"(r[1]), "=r"(r[2]), "=r"(r[3]) : "r"(a) : "memory");
}
__device__ __forceinline__ void ldsm4t(uint32_t (&r)[4], uint32_t a) {
  asm volatile("ldmatrix.sync.aligned.m8n8.x4.trans.shared.b16 {%0,%1,%2,%3}, [%4];"
               : "=r"(r[0]), "=r"(r[1]), "=r"(r[2]), "=r"(r[3]) : "r"(a) : "memory");
}
__device__ __forceinline__ uint32_t ldsm1t(uint32_t a) {
  uint32_t r;
  asm volatile("ldmatrix.sync.aligned.m8n8.x1.trans.shared.b16 {%0}, [%1];" : "=r"(r) : "r"(a) : "memory");
  return r;
}
__device__ __forceinline__ void stsm4t(uint32_t a, uint32_t r0, uint32_t r1, uint32_t r2, uint32_t r3) {
  asm volatile("stmatrix.sync.aligned.m8n8.x4.trans.shared.b16 [%0], {%1,%2,%3,%4};"
               ::"r"(a), "r"(r0), "r"(r1), "r"(r2), "r"(r3) : "memory");
}
__device__ __forceinline__ uint32_t lds32v(uint32_t a) {
  uint32_t v; asm volatile("ld.volatile.shared.b32 %0, [%1];" : "=r"(v) : "r"(a) : "memory"); return v;
}
__device__ __forceinline__ uint2 lds64(uint32_t a) {
  uint2 v; asm volatile("ld.shared.v2.b32 {%0,%1}, [%2];" : "=r"(v.x), "=r"(v.y) : "r"(a) : "memory"); return v;
}
__device__ __forceinline__ uint4 lds128(uint32_t a) {
  uint4 v; asm volatile("ld.shared.v4.b32 {%0,%1,%2,%3}, [%4];" : "=r"(v.x), "=r"(v.y), "=r"(v.z), "=r"(v.w) : "r"(a) : "memory");
  return v;
}
__device__ __forceinline__ void sts32(uint32_t a, uint32_t v) { asm volatile("st.shared.b32 [%0], %1;" ::"r"(a), "r"(v) : "memory"); }
__device__ __forceinline__ void sts64(uint32_t a, uint32_t x, uint32_t y) {
  asm volatile("st.shared.v2.b32 [%0], {%1,%2};" ::"r"(a), "r"(x), "r"(y) : "memory");
}
__device__ __forceinline__ void sts128(uint32_t a, uint32_t x, uint32_t y, uint32_t z, uint32_t w) {
  asm volatile("st.shared.v4.b32 [%0], {%1,%2,%3,%4};" ::"r"(a), "r"(x), "r"(y), "r"(z), "r"(w) : "memory");
}
__device__ __forceinline__ uint32_t pack2(float lo, float hi) {
  uint32_t r; asm("cvt.rn.bf16x2.f32 %0, %1, %2;" : "=r"(r) : "f"(hi), "f"(lo)); return r;
}
__device__ __forceinline__ uint32_t packh(float lo, float hi) {
  uint32_t r; asm("cvt.rn.f16x2.f32 %0, %1, %2;" : "=r"(r) : "f"(hi), "f"(lo)); return r;
}
__device__ __forceinline__ uint32_t hmul2(uint32_t a, uint32_t b) {
  uint32_t r; asm("mul.rn.f16x2 %0, %1, %2;" : "=r"(r) : "r"(a), "r"(b)); return r;
}
__device__ __forceinline__ uint32_t hfma2(uint32_t a, uint32_t b, uint32_t c) {
  uint32_t r; asm("fma.rn.f16x2 %0, %1, %2, %3;" : "=r"(r) : "r"(a), "r"(b), "r"(c)); return r;
}
__device__ __forceinline__ uint32_t bfma2(uint32_t a, uint32_t b, uint32_t c) {
  uint32_t r; asm("fma.rn.bf16x2 %0, %1, %2, %3;" : "=r"(r) : "r"(a), "r"(b), "r"(c)); return r;
}
__device__ __forceinline__ uint32_t bmul2(uint32_t a, uint32_t b) { return bfma2(a, b, 0x80008000u); }
__device__ __forceinline__ uint32_t badd2(uint32_t a, uint32_t b) { return bfma2(a, 0x3f803f80u, b); }
__device__ __forceinline__ float bf_lo(uint32_t v) { return __uint_as_float(v << 16); }
__device__ __forceinline__ float bf_hi(uint32_t v) { return __uint_as_float(v & 0xffff0000u); }
__device__ __forceinline__ float bf_round(float v) { return __uint_as_float(pack2(0.f, v)); }
__device__ __forceinline__ uint32_t ldg_u16(const __nv_bfloat16* p) {
  uint32_t v; asm volatile("ld.global.nc.u16 %0, [%1];" : "=r"(v) : "l"(p)); return v;
}
__device__ __forceinline__ float2 cmul(float2 a, float2 b) {
  return make_float2(fmaf(a.x, b.x, -a.y * b.y), fmaf(a.x, b.y, a.y * b.x));
}
__device__ __forceinline__ float2 cexp_p(float zr2, float zi, float p) {
  float m; asm("ex2.approx.ftz.f32 %0, %1;" : "=f"(m) : "f"(zr2 * p));
  const float x = zi * p;
  const float k = __fadd_rn(fmaf(x, 0.15915494309189535f, 12582912.f), -12582912.f);
  float r = fmaf(-k, 6.2831854820251465f, x);
  r = fmaf(-k, -1.7484555314695172e-7f, r);
  return make_float2(m * __cosf(r), m * __sinf(r));
}
__device__ __forceinline__ float2 csqr(float2 a) { return make_float2(fmaf(a.x, a.x, -a.y * a.y), (a.x + a.x) * a.y); }
struct H2 { uint32_t r, i; };
struct H2S { uint32_t r, i, ni; };
__device__ __forceinline__ H2 pack_c(float2 a, float2 b) { return {packh(a.x, b.x), packh(a.y, b.y)}; }
__device__ __forceinline__ H2S bcast_c(float2 a) {
  const uint32_t i = packh(a.y, a.y);
  return {packh(a.x, a.x), i, i ^ 0x80008000u};
}
__device__ __forceinline__ H2 hcmul(H2 a, H2S s) {
  return {hfma2(a.r, s.r, hmul2(a.i, s.ni)), hfma2(a.r, s.i, hmul2(a.i, s.r))};
}
__device__ __forceinline__ void sts_row(uint32_t a, H2 p0, H2 p1, H2 p2, H2 p3) {
  sts128(a, p0.r, p1.r, p2.r, p3.r);
  sts128(a + 512, p0.i, p1.i, p2.i, p3.i);
}
__device__ __forceinline__ void sts_acc(uint32_t a, const float (&c)[2][4]) {
  sts128(a, packh(c[0][0], c[0][1]), packh(c[0][2], c[0][3]), packh(c[1][0], c[1][1]), packh(c[1][2], c[1][3]));
}
__device__ __forceinline__ float2 unpackh(uint32_t v) {
  float2 r;
  asm("{\n.reg .f16 l, h;\nmov.b32 {l, h}, %2;\ncvt.f32.f16 %0, l;\ncvt.f32.f16 %1, h;\n}" : "=f"(r.x), "=f"(r.y) : "r"(v));
  return r;
}

struct Params {
  const __nv_bfloat16 *log_a, *a_im, *c_re, *c_im, *log_dt, *d_skip, *gate_w;
};

template <class F>
__device__ __forceinline__ void kgen_task(uint32_t st, uint32_t st2, uint32_t kl_addr, int lane, float lar, float aim,
                                          float cre, float cim, float ldt, F mid) {
  const float dt = bf_round(expf(ldt));
  const float zr2 = -bf_round(__expf(lar)) * dt * 1.4426950408889634f;
  const float zi = aim * dt;
  const float2 w1 = cexp_p(zr2, zi, 1.f), w128 = cexp_p(zr2, zi, 128.f);
  const uint32_t ex = max(__reduce_max_sync(0xffffffffu, __float_as_uint(fmaxf(fabsf(cre), fabsf(cim)))) >> 23, 7u);
  const float scale = __uint_as_float((260u - ex) << 23);
  const float2 c = make_float2(cre * scale, cim * scale);
  const uint32_t row = st + lane * 16, row2 = st2 + lane * 16;
  if (lane == 0) sts32(kl_addr, ex);

  const float2 w2 = csqr(w1), w4 = csqr(w2), w8 = csqr(w4);
  {
    const float2 s8 = make_float2(w8.x, -w8.y), s16 = csqr(s8), s32 = csqr(s16), s64 = csqr(s32);
    const H2 p0 = pack_c(make_float2(1.f, 0.f), s8), p1 = pack_c(s16, cmul(s16, s8));
    const H2S b32 = bcast_c(s32);
    sts_row(row, p0, p1, hcmul(p0, b32), hcmul(p1, b32));
    const uint32_t p = packh(s64.x, s64.y);
    asm volatile("st.shared.b16 [%0], %1;\nst.shared.b16 [%0+64], %2;"
                 ::"r"(st + 2048 + lane * 2), "h"((uint16_t)p), "h"((uint16_t)(p >> 16)) : "memory");
  }
  mid();
  __syncwarp();
  H2 x[4][4];
  uint32_t sr[4], si[4], br[4], bi[4];
  ldsm4(sr, st + 2048 + (lane >> 3) * 16);
  ldsm4(si, st + 2048 + 64 + (lane >> 3) * 16);
#pragma unroll
  for (int m = 0; m < 4; m++) x[0][m] = {ldsm1t(row + m * 128), ldsm1t(row + m * 128 + 512)};
  const float2 c1 = cmul(c, w1), c2 = cmul(c, w2), c3 = cmul(c1, w2), c4 = cmul(c, w4), c8 = cmul(c, w8);
  const H2 p26 = pack_c(c2, cmul(c2, w4)), p48 = pack_c(c4, c8);
  sts_row(row + 1024, pack_c(c1, cmul(c1, w4)), p26, pack_c(c3, cmul(c3, w4)), p48);
  __syncwarp();
  ldsm4t(br, row + 1024);
  ldsm4t(bi, row + 1536);
  const float2 w256 = csqr(w128);
  const H2S b256 = bcast_c(w256);
  {
    const H2 q1 = hcmul(p48, b256), q2 = hcmul(q1, b256);
    sts_row(row2, hcmul(p26, b256), q1, q2, hcmul(q2, b256));
  }
#pragma unroll
  for (int m = 0; m < 4; m++) {
    const H2S s = {sr[m], si[m], si[m] ^ 0x80008000u};
#pragma unroll
    for (int t = 1; t < 4; t++) x[t][m] = hcmul(x[t - 1][m], s);
  }
  auto tile = [&](float (&acc)[2][4], int nm) {
#pragma unroll
    for (int i = 0; i < 8; i++) acc[i >> 2][i & 3] = 0.f;
#pragma unroll
    for (int h = 0; h < 4; h += 2) {
#pragma unroll
      for (int mt = 0; mt < 2; mt++)
        if (mt < nm) mma_f16(acc[mt], x[2 * mt][h].r, x[2 * mt + 1][h].r, x[2 * mt][h + 1].r, x[2 * mt + 1][h + 1].r, br[h], br[h + 1]);
#pragma unroll
      for (int mt = 0; mt < 2; mt++)
        if (mt < nm) mma_f16(acc[mt], x[2 * mt][h].i, x[2 * mt + 1][h].i, x[2 * mt][h + 1].i, x[2 * mt + 1][h + 1].i, bi[h], bi[h + 1]);
    }
  };
  float a0[2][4], a1[2][4], a2[2][4];
  tile(a0, 2);
  __syncwarp();
  ldsm4t(br, row2);
  ldsm4t(bi, row2 + 512);
  {
    const float2 f = cmul(c8, csqr(csqr(w256)));
    const H2 q0 = pack_c(f, cmul(f, w128)), q1 = hcmul(q0, b256), q2 = hcmul(q1, b256);
    sts_row(row2 + 1024, q0, q1, q2, hcmul(q2, b256));
  }
  tile(a1, 2);
  __syncwarp();
  ldsm4t(br, row2 + 1024);
  ldsm4t(bi, row2 + 1536);
  sts_acc(row, a0);
  tile(a2, 1);
  sts_acc(row + 512, a1);
  sts64(st + 1024 + lane * 8, packh(a2[0][0], a2[0][1]), packh(a2[0][2], a2[0][3]));
}

template <int I0, int I1>
__device__ __forceinline__ void swiglu_packed(const float (&ag)[88], const float (&au)[88], uint32_t a) {
#pragma unroll
  for (int i = I0; i < I1; i += 8) {
    uint32_t p[4];
#pragma unroll
    for (int k = 0; k < 4; k++) {
      const uint32_t hg = bmul2(pack2(ag[i + 2 * k], ag[i + 2 * k + 1]), 0x3f003f00u);
      uint32_t t;
      asm("tanh.approx.bf16x2 %0, %1;" : "=r"(t) : "r"(hg));
      p[k] = bmul2(bfma2(hg, t, hg), pack2(au[i + 2 * k], au[i + 2 * k + 1]));
    }
    stsm4t(a + i * 256, p[0], p[1], p[2], p[3]);
  }
}
__device__ __forceinline__ void swiglu_store(float (&ag)[88], float (&au)[88], uint32_t a, int wg) {
  bar_sync(NB_OUT + 2 * wg, 128);
  swiglu_packed<0, 16>(ag, au, a);
  bar_arrive_pinned(NB_H + 4 * wg, 160);
  swiglu_packed<16, 40>(ag, au, a);
  bar_arrive_pinned(NB_H + 4 * wg + 1, 160);
  swiglu_packed<40, 64>(ag, au, a);
  bar_arrive_pinned(NB_H + 4 * wg + 2, 160);
  swiglu_packed<64, 88>(ag, au, a);
  bar_arrive(NB_H + 4 * wg + 3, 160);
}

__device__ __forceinline__ uint32_t loads_done(uint32_t sb) {
  __syncwarp();
  return lds32v(sb + kOffZero);
}

__device__ __forceinline__ void conv(uint32_t sb, uint32_t pbars, int cta, int w, int lane) {
  const uint32_t bars = sb + kOffBar;
  const uint32_t ub = sb + kOffU, tb = sb + kOffTaps + w * 4096, vb = sb + kOffV + w * kVChan;
  const int mi = lane >> 3, n8 = lane & 7;
  const uint32_t tx = (lane >> 2) - 2 * (lane & 3);
  float acc[16][4];
  {
    const uint32_t ia = sb + kOffI + w * kIChan + (mi & 1) * 1536 + (mi >> 1) * 128 + n8 * 16;
#pragma unroll
    for (int j = 0; j < 16; j += 2) {
      uint32_t v[4] = {0u, 0u, 0u, 0u};
      if (j >= 4) ldsm4t(v, ia + (j - 4) * 128);
#pragma unroll
      for (int e = 0; e < 4; e++) {
        acc[j + (e >> 1)][2 * (e & 1)] = bf_lo(v[e]);
        acc[j + (e >> 1)][2 * (e & 1) + 1] = bf_hi(v[e]);
      }
    }
  }
  const uint32_t ta = tb + (tx + 16) * 4;
  auto load_t = [&](uint32_t (&T)[4], uint32_t a) {
    T[0] = lds32v(a); T[1] = lds32v(a + 32); T[2] = lds32v(a - 32); T[3] = lds32v(a);
  };
  auto load_near = [&](uint32_t (&T)[4][4], uint32_t (&g)[8][4], int rho) {
    const int row = 8 * (mi >> 1) + 8 - rho + n8;
    const uint32_t ga = ub + row * 128 + (((2 * w + (mi & 1)) ^ (row & 7)) << 4);
#pragma unroll
    for (int i = 0; i < 8; i++) {
      ldsm4(g[i], ga + i * 2048);
      if (i < 4) load_t(T[i], ta + rho * 64 + i * 512);
    }
  };
  uint32_t T0[4][4], g0[8][4], T1[4][4], g1[8][4], T4[4];
  {
    uint2 pa[5], pb[5], pc[8];
#pragma unroll
    for (int h = 0; h < 5; h++) {
      pa[h] = lds64(tb + kTapA + (tx + 8 + 8 * h) * 8);
      pb[h] = lds64(tb + kTapB + (tx + 8 + 8 * h) * 8);
    }
#pragma unroll
    for (int h = 0; h < 8; h++) pc[h] = lds64(tb + kTapC + (tx + 8 + 8 * h) * 8);
    const uint32_t qa = vb + (mi >> 1) * kV5e + n8 * 16 + ((mi & 1) ? kV3o : kV3e);
    const uint32_t qb = vb + (mi >> 1) * kV5e + n8 * 16 + ((mi & 1) ? kV3e : kV3o - 16);
    const uint32_t qb0 = (lane & 15) == 0 ? ub : qb;
    const uint32_t qc = vb + kV7e + mi * 1024 + n8 * 16;
    uint32_t va[12][4], vb8[12][4], vc[8][4];
    auto load = [&](int s) {
      ldsm4t(va[s], qa + s * 128);
      ldsm4t(vb8[11 - s], s < 11 ? qb + (11 - s) * 128 : qb0);
      if (s < 8) ldsm4t(vc[7 - s], qc + (7 - s) * 128);
    };
    load(0);
    mbar_wait(bars + B_P1 * 8, 0);
#pragma unroll
    for (int s = 0; s < 12; s++) {
      if (s < 11) load(s + 1);
      if (s == 0) {
        const uint32_t z = loads_done(sb);
        if (lane == 0) mbar_arrive(bars + B_RDYI * 8 + z);
      }
      if (s == 10) {
        const uint32_t z = loads_done(sb);
        if (lane < 2) mbar_arrive_mapped(pbars + B_RDYB * 8 + z);
        load_near(T0, g0, 7);
        load_t(T4, ta + 2048);
      }
#pragma unroll
      for (int h = 7; h >= 0; h--)
        if (s < 8 && h <= s) mma_bf16(acc[15 - s + h], vc[7 - s][0], vc[7 - s][1], vc[7 - s][2], vc[7 - s][3], pc[h].x, pc[h].y);
#pragma unroll
      for (int h = 0; h < 5; h++)
        if (s + h < 12) mma_bf16(acc[s + h + 4], va[s][0], va[s][1], va[s][2], va[s][3], pa[h].x, pa[h].y);
#pragma unroll
      for (int h = 4; h >= 0; h--)
        if (h <= s) mma_bf16(acc[15 - s + h], vb8[11 - s][0], vb8[11 - s][1], vb8[11 - s][2], vb8[11 - s][3], pb[h].x, pb[h].y);
    }
  }
  uint8_t* dst = g_aT + (size_t)(cta * 4 + w) * 4096 + ((lane ^ (w << 2)) << 3);
  auto store = [&](int j) {
    uint32_t p[2];
#pragma unroll
    for (int h = 0; h < 2; h++) {
      p[h] = pack2(acc[j][2 * h], acc[j][2 * h + 1]);
      asm volatile("movmatrix.sync.aligned.m8n8.trans.b16 %0, %0;" : "+r"(p[h]));
    }
    *reinterpret_cast<uint2*>(dst + j * 256) = make_uint2(p[0], p[1]);
  };
  {
    auto group = [&](const uint32_t (&T)[4], const uint32_t (&g)[8][4], int e, int j0, int j1) {
#pragma unroll
      for (int s = 0; s + e < 16; s++)
        if (s + e >= j0 && s + e < j1)
          mma_bf16(acc[s + e], T[0], T[1], T[2], T[3], g[s >> 1][2 * (s & 1)], g[s >> 1][2 * (s & 1) + 1]);
    };
#pragma unroll
    for (int rho = 7; rho > 1; rho -= 2) {
      load_near(T1, g1, rho - 1);
#pragma unroll
      for (int e = 0; e < 4; e++) group(T0[e], g0, e, 0, 16);
      load_near(T0, g0, rho - 2);
#pragma unroll
      for (int e = 0; e < 4; e++) group(T1[e], g1, e, 0, 16);
    }
    load_near(T1, g1, 0);
#pragma unroll
    for (int e = 0; e < 3; e++) group(T0[e], g0, e, 0, 16);
    const uint32_t z = loads_done(sb);
    if (lane < 2) mbar_arrive_mapped(pbars + B_RDYD * 8 + z);
    sched_fence();
#pragma unroll
    for (int part = 0; part < 2; part++) {
      const int j0 = part ? kEarly : 0, j1 = part ? 16 : kEarly;
      group(T0[3], g0, 3, j0, j1);
#pragma unroll
      for (int e = 0; e < 4; e++) group(T1[e], g1, e, j0, j1);
      group(T4, g1, 4, j0, j1);
      if (part == 0) {
#pragma unroll
        for (int j = 0; j < kEarly; j++) store(j);
      }
    }
  }
  bar_arrive_pinned(NB_CONV, 256);
#pragma unroll
  for (int j = kEarly; j < 16; j++) {
    store(j);
    if ((j & 1) && j < 15) __nanosleep(20);
  }
  bar_arrive(NB_AST, 160);
}

__device__ __forceinline__ void issue_stage(uint32_t sb, int step, int slot, const CUtensorMap* mx, const CUtensorMap* mw,
                                            int ft, int tt, uint32_t rank) {
  const uint32_t bar = sb + kOffBar + slot * 8, dst = sb + slot * kUnit + rank * 4096;
  mbar_expect(bar, kStageBytes);
  tma2d_mc(dst, mw, ft * 128, step * 32, bar);
  tma2d_mc(dst + kOffW1, mw, ft * 128 + 64, step * 32, bar);
  tma2d(sb + kOffX + slot * kStageX, mx, step * 32, tt * kTok1, bar);
}
__device__ __forceinline__ void issue_p1(uint32_t sb, int step0, int step1, const CUtensorMap* mx, const CUtensorMap* mw,
                                         int ft, int tt, uint32_t rank) {
#pragma unroll 1
  for (int step = step0; step < step1; step++) {
    const int slot = (step + 4) % 5;
    if (step >= 5) mbar_wait(sb + kOffBar + (B_EMPTY1 + slot) * 8, step >= 10 && step < 15);
    issue_stage(sb, step, slot, mx, mw, ft, tt, rank);
  }
}

template <int K>
__device__ __forceinline__ void load_w_regs(uint32_t (&wr)[kRegW * 4][4], uint32_t a) {
  constexpr uint32_t off = (kSched[K] & 31) * kUnit;
#pragma unroll
  for (int i = 0; i < 4; i++) ldsm4t(wr[4 * K + i], a + off + i * 2048);
  if constexpr (K + 1 < kRegW) {
    __nanosleep(128);
    load_w_regs<K + 1>(wr, a);
  }
}

template <int K>
__device__ __forceinline__ void p2_steps(float (&d)[64], const uint32_t (&wr)[kRegW * 4][4], uint32_t bars,
                                         uint32_t pbars, bool leader, uint32_t ready) {
  constexpr uint32_t e = kSched[K];
  const uint64_t dw = make_desc((e & 31) * kUnit, 1024, 1), dh = make_desc(((e >> 5) & 31) * kUnit, 1024, 1);
  if (__builtin_expect(!ready, 0)) mbar_wait(bars + (B_FULL2 + K) * 8, 0);
  if (K + 1 < kNumFt) ready = mbar_test(bars + (B_FULL2 + K + 1) * 8, 0);
  wg_fence();
  auto mma = [&](int i) {
    if constexpr (K < kRegW) wgmma_n128_rs(d, wr[4 * K + i], dh + 2 * i, K | i);
    else wgmma_n128(d, dw + 128 * i, dh + 2 * i, K | i);
  };
  mma(0);
  mma(1);
  if (K >= 1 && K <= kNumCons) {
    wg_commit();
    wg_wait<1>();
    if (leader) mbar_arrive_mapped(pbars + (B_CONS + K - 1) * 8);
  }
  if constexpr (K + 1 < kNumFt) {
    mma(2);
    mma(3);
    wg_commit();
    p2_steps<K + 1>(d, wr, bars, pbars, leader, ready);
  } else {
    wg_commit();
  }
}

template <int I>
__device__ __forceinline__ void load_w(uint32_t sb, const CUtensorMap* m, int col) {
  constexpr uint32_t e = kSched[I], k = (e >> 16) & 31;
  if ((e >> 26) != 63) mbar_wait(sb + kOffBar + (e >> 26) * 8, 0);
  tma2d(sb + ((e >> 21) & 31) * kUnit, m, col, p2_tile(k) * 64, sb + kOffBar + (k < kRegW ? B_WR : B_FULL2 + k) * 8);
  if constexpr (I + 1 < kNumFt) load_w<I + 1>(sb, m, col);
}

template <int K>
__device__ __forceinline__ void load_h(uint32_t sb, uint32_t dst, const uint8_t* src, const uint16_t* gate) {
  constexpr uint32_t e = kSched[K], wb = (e >> 10) & 63;
  if (K == 2) bulk_load(sb + kOffGate, gate, 256, sb + kOffBar + B_G * 8);
  if (K == 10) {
    mbar_wait(sb + kOffBar + B_H0 * 8, 0);
    fence_async_gmem();
  }
  if (wb != 63) mbar_wait(sb + kOffBar + wb * 8, 0);
  bulk_load_mc(dst + ((e >> 5) & 31) * kUnit, src + (size_t)p2_tile(K) * kL * 128, 8192, sb + kOffBar + (B_FULL2 + K) * 8);
  if constexpr (K + 1 < kNumFt) load_h<K + 1>(sb, dst, src, gate);
}

__device__ __forceinline__ void store_h(uint32_t sb, int wg, int ft, int tt) {
  const uint32_t src = sb + kOffHs + wg * kOffW1;
  uint8_t* dst = g_H + ((size_t)(2 * ft + wg) * kL + tt * kTok1) * 128;
  const int bytes = (tt == 11 ? kL - 11 * kTok1 : kTok1) * 128;
  int done = 0;
#pragma unroll 1
  for (int i = 0; i < 4; i++) {
    const int end = min(bytes, ((16 | 40 << 8 | 64 << 16 | 88 << 24) >> (8 * i) & 255) * 256);
    bar_sync(NB_H + 4 * wg + i, 160);
    fence_async_smem();
    if (end > done && elect()) bulk_store(dst + done, src + done, end - done);
    done = end;
  }
  if (elect()) {
    bulk_commit();
    bulk_wait();
    mbar_arrive_pair(sb + kOffBar + (B_RDYA0 + wg) * 8);
    cnt_add(C_H + wg, 1ull << (5 * tt));
    if (wg == 0) {
      mbar_arrive(sb + kOffBar + B_F0 * 8);
      mbar_arrive(sb + kOffBar + B_F0 * 8);
    }
  }
  __syncwarp();
}

__global__ void __cluster_dims__(2, 1, 1) __launch_bounds__(kThreads, 1)
fused_kernel(const __grid_constant__ Params prm, const __grid_constant__ CUtensorMap map_x,
             const __grid_constant__ CUtensorMap map_wg,
             const __grid_constant__ CUtensorMap map_wu, const __grid_constant__ CUtensorMap map_wd,
             const __grid_constant__ CUtensorMap map_ut, const __grid_constant__ CUtensorMap map_out,
             const __grid_constant__ CUtensorMap map_xr, const __grid_constant__ CUtensorMap map_a) {
  extern __shared__ __align__(1024) uint8_t smem[];
  const int pi = (blockIdx.x & 127) * 512 + threadIdx.x;
  const uint32_t lar = ldg_u16(prm.log_a + pi), ldt = ldg_u16(prm.log_dt + (pi >> 7));
  const uint32_t aim = ldg_u16(prm.a_im + pi), cre = ldg_u16(prm.c_re + pi), cim = ldg_u16(prm.c_im + pi);
  const uint32_t sb = __shfl_sync(0xffffffffu, (uint32_t)__cvta_generic_to_shared(smem), 0);
  const uint32_t bars = sb + kOffBar;
  const int tid = threadIdx.x, lane = tid & 31;
  const int warp = __shfl_sync(0xffffffffu, tid >> 5, 0);
  const int cta = blockIdx.x, cid = cta >> 1;
  const uint32_t rank = cta & 1;
  const int ft = cid % 11, tt = (cid / 11) * 2 + rank;
  const int tj = (cid & 7) + ((cid >> 5) & 1) * 8, dt = ((cid >> 3) & 3) * 2 + rank;
  const bool full_cta = cta < 128;

  const int blk = 11 * tt + ft;
  const CUtensorMap* map_w = rank ? &map_wu : &map_wg;
  static_assert(B_COUNT <= 64, "barrier page");
  if (warp >= 12) {
    if (elect()) {
#pragma unroll
      for (int i = 0; i < 16; i++)
        mbar_init(bars + ((warp - 12) * 16 + i) * 8, warp == 12 ? (uint32_t)(kBarCounts >> (4 * i)) & 15u : 2u);
      asm volatile("fence.mbarrier_init.release.cluster;" ::: "memory");
    }
    __syncwarp();
  }
  asm volatile("barrier.cluster.arrive.relaxed.aligned;" ::: "memory");
  const bool early = warp == 12 || warp == 13;
  auto first_loads = [&](int s0, int s1) {
    asm volatile("barrier.cluster.wait.aligned;" ::: "memory");
    if (elect()) {
      if (s0 && blk < 128) {
        mbar_expect(bars + B_XR * 8, 17408);
        tma3d(sb + kOffU, &map_xr, 0, blk * 16, 0, bars + B_XR * 8);
        bulk_load(sb + kOffGate, prm.gate_w, 1024, bars + B_XR * 8);
      }
#pragma unroll
      for (int s = s0; s < s1; s++) issue_stage(sb, s, (s + 4) % 5, &map_x, map_w, ft, tt, rank);
    }
    __syncwarp();
  };
  if (warp == 12) first_loads(0, 2);
  if ((tid & 127) == 0) sts32(sb + kOffZero, 0u);
  auto mid = [&]() { if (warp == 13) first_loads(2, 4); };
  if (full_cta)
    kgen_task(sb + kOffV + warp * kPart, sb + (warp < 8 ? kOffI : kOffTaps - 16384) + warp * 2048, sb + kOffKl + warp * 4,
              lane, bf_lo(lar), bf_lo(aim), bf_lo(cre), bf_lo(cim), bf_lo(ldt), mid);
  else
    mid();

  if (warp < 8) {
    bar_arrive(NB_KGEN, kThreads);
    asm volatile("barrier.cluster.wait.aligned;" ::: "memory");
    mbar_wait(bars + (B_FULL1 + 4) * 8, 0);
    asm volatile("setmaxnreg.inc.sync.aligned.u32 208;");
    const int wg = warp >> 2, wq = warp & 3;
    const bool leader = (tid & 126) == 0;
    uint32_t pbars;
    asm("mapa.shared::cluster.u32 %0, %1, %2;" : "=r"(pbars) : "r"(bars), "r"(tid & 1));
    const int mi = lane >> 3, n8 = lane & 7;
    {
      float ag[88], au[88];
      const uint64_t dg0 = make_desc(wg * kOffW1, 1024, 1), dx0 = make_desc(kOffX, 512, 2);
      auto mma_step = [&](uint32_t slot, int acc) {
        const uint64_t dg = dg0 + slot * (kUnit >> 4), dx = dx0 + slot * (kStageX >> 4);
        wg_fence();
        wgmma_n176(ag, dg, dx, acc);
        wgmma_n176(au, dg + 256, dx, acc);
        wg_commit();
        wgmma_n176(ag, dg + 128, dx + 2, 1);
        wgmma_n176(au, dg + 384, dx + 2, 1);
        wg_commit();
      };
      mma_step(4, 0);
      uint32_t ready = 0, par = 0, prev = 4, slot = 0;
      const int pause = wg ? -1 : kSkew;
#pragma unroll 1
      for (int step = 1; step < 16; step++) {
        if (step == pause) {
          wg_wait<0>();
          if (leader) mbar_arrive_mapped(pbars + (B_EMPTY1 + prev) * 8);
          mbar_wait(bars + B_SKEW * 8, 0);
        }
        if (!ready) mbar_wait(bars + (B_FULL1 + slot) * 8, par);
        const uint32_t next = slot == 4 ? 0 : slot + 1;
        par ^= slot == 3;
        ready = mbar_test(bars + (B_FULL1 + next) * 8, par);
        mma_step(slot, 1);
        wg_wait<2>();
        if (leader && step != pause) mbar_arrive_mapped(pbars + (B_EMPTY1 + prev) * 8);
        if (leader && step == 13 && wg) mbar_arrive(bars + B_W1 * 8);
        prev = slot;
        slot = next;
      }
      wg_wait<1>();
      if (leader && wg) mbar_arrive(bars + B_SKEW * 8);
      wg_wait<0>();
      if (tid == 0) mbar_arrive(bars + B_P1 * 8);
      const uint32_t a = sb + kOffHs + wg * kOffW1 + ((mi >> 1) * 8 + n8) * 128 + (((2 * wq + (mi & 1)) ^ n8) << 4);
      swiglu_store(ag, au, a, wg);
    }
    if (wg == 0) {
      if (full_cta) {
        float d[64];
        const uint32_t aa = sb + kOffA + (16 * wq + (lane >> 2)) * 256 + (lane & 15) * 8;
        const uint32_t oa = sb + kOffOut + ((mi >> 1) * 8 + n8) * 128 + (((2 * wq + (mi & 1)) ^ n8) << 4);
        uint32_t wr[kRegW * 4][4];
        mbar_wait(bars + B_WR * 8, 0);
        load_w_regs<0>(wr, oa - kOffOut);
        bar_sync(NB_OUT + loads_done(sb), 128);
        if (leader) mbar_arrive_mapped(pbars + B_WRD * 8);
        uint4 g[4];
        mbar_wait(bars + B_G * 8, 0);
#pragma unroll
        for (int i = 0; i < 4; i++) g[i] = lds128(sb + kOffGate + (lane & 3) * 16 + i * 64);
        mbar_wait(bars + B_FULL2 * 8, 0);
        bar_sync(NB_CONV, 256);
        p2_steps<0>(d, wr, bars, pbars, leader, 1);
        mbar_wait(bars + B_A * 8, 0);
        uint32_t pa[8][4], og[8][2];
#pragma unroll
        for (int i = 0; i < 8; i++) {
          const uint2 a0 = lds64(aa ^ (i << 5)), a1 = lds64((aa ^ (i << 5)) + 2048);
          const uint32_t g0 = (i & 1) ? g[i >> 1].z : g[i >> 1].x, g1 = (i & 1) ? g[i >> 1].w : g[i >> 1].y;
          og[i][0] = bfma2(g0, 0xbf80bf80u, 0x3f803f80u);
          og[i][1] = bfma2(g1, 0xbf80bf80u, 0x3f803f80u);
          pa[i][0] = bmul2(a0.x, g0);
          pa[i][1] = bmul2(a1.x, g0);
          pa[i][2] = bmul2(a0.y, g1);
          pa[i][3] = bmul2(a1.y, g1);
        }
        wg_wait<0>();
#pragma unroll
        for (int i = 0; i < 8; i++) {
#pragma unroll
          for (int e = 0; e < 4; e++) pa[i][e] = bfma2(og[i][e >> 1], pack2(d[8 * i + 2 * e], d[8 * i + 2 * e + 1]), pa[i][e]);
          stsm4t(oa + i * 2048, pa[i][0], pa[i][1], pa[i][2], pa[i][3]);
          if (i == 3) bar_arrive_pinned(NB_AST, 160);
        }
        bar_arrive(NB_CONV, 160);
      } else {
        asm volatile("barrier.cluster.arrive.relaxed.aligned;" ::: "memory");
        asm volatile("barrier.cluster.wait.aligned;" ::: "memory");
      }
    } else if (full_cta) {
      bar_sync(NB_PREP, 256);
      conv(sb, pbars, cta, wq, lane);
    }
  } else if (warp < 12) {
    asm volatile("setmaxnreg.dec.sync.aligned.u32 72;");
    asm volatile("barrier.cluster.wait.aligned;" ::: "memory");
    const int w = warp - 8, mi = lane >> 3, n8 = lane & 7, r = lane >> 2, q = lane & 3;
    const uint32_t ub = sb + kOffU, tb = sb + kOffTaps + w * 4096, vb = sb + kOffV + w * kVChan;
    const int chan = (cta & 127) * 4 + w;
    const uint32_t dsk = ldg_u16(prm.d_skip + chan), ldw = ldg_u16(prm.log_dt + chan);
    const uint2 crw = __ldg(reinterpret_cast<const uint2*>(prm.c_re + chan * 128) + lane);
    if (blk < 128) {
      mbar_wait(bars + B_XR * 8, 0);
      const int tok = (n8 >> 1) * 4 + (n8 & 1) + 2 * ((mi ^ (n8 >> 2)) & 1);
      const uint32_t a = ub + w * 4096 + tok * 128 + (((mi >> 1) ^ (tok & 7)) << 4);
      uint8_t* dst = g_uT + (size_t)blk * 16384 + (w * 128 + r) * 32 + q * 8;
      const bool sw = q & 2;
#pragma unroll 1
      for (int h = 0; h < 2; h++) {
#pragma unroll
        for (int c = 0; c < 8; c += 2) {
          uint32_t v[4];
          ldsm4t(v, (a ^ (c << 4)) + h * 2048);
          *reinterpret_cast<uint2*>(dst + h * 2048 + c * 256) = make_uint2(sw ? v[1] : v[0], sw ? v[0] : v[1]);
          *reinterpret_cast<uint2*>(dst + h * 2048 + c * 256 + 256) = make_uint2(sw ? v[3] : v[2], sw ? v[2] : v[3]);
        }
      }
      bar_arrive(NB_WG2, 160);
      const int t = 4 * w + mi;
      const uint32_t xa = ub + t * 128 + ((n8 ^ (t & 7)) << 4), wa = sb + kOffGate + n8 * 16;
      float s = 0.f;
#pragma unroll 1
      for (int c = 0; c < 8; c++) {
        const uint4 x = lds128(xa + c * 2048), gw = lds128(wa + c * 128);
        const uint32_t m0 = bmul2(x.x, gw.x), m1 = bmul2(x.y, gw.y), m2 = bmul2(x.z, gw.z), m3 = bmul2(x.w, gw.w);
        s += ((bf_lo(m0) + bf_hi(m0)) + (bf_lo(m1) + bf_hi(m1))) + ((bf_lo(m2) + bf_hi(m2)) + (bf_lo(m3) + bf_hi(m3)));
      }
#pragma unroll
      for (int o = 1; o < 8; o <<= 1) s += __shfl_xor_sync(0xffffffffu, s, o);
      if (n8 == 0)
        g_gate[(blk >> 1) * 32 + ((t >> 1) & 3) * 8 + ((blk & 1) * 2 + (t >> 3)) * 2 + (t & 1)] =
            (uint16_t)pack2(__fdividef(1.f, 1.f + __expf(-bf_round(s))), 0.f);
      bar_arrive(NB_GATE, 192);
    }
    if (!full_cta) {
      bar_arrive(NB_KGEN, kThreads);
      return;
    }
    uint32_t k512, k1024;
    {
      float k0 = (bf_lo(crw.x) + bf_hi(crw.x)) + (bf_lo(crw.y) + bf_hi(crw.y));
#pragma unroll
      for (int o = 1; o < 32; o <<= 1) k0 += __shfl_xor_sync(0xffffffffu, k0, o);
      const float dt2 = 2.f * bf_round(expf(bf_lo(ldw)));
      k0 = fmaf(dt2, k0, bf_lo(dsk));
      bar_sync(NB_KGEN, kThreads);
      float k[5][4];
      const uint4 l0 = lds128(sb + kOffKl + w * 16);
      const uint32_t em = max(max(l0.x, l0.y), max(l0.z, l0.w));
      const float sc = __uint_as_float((em - 6u) << 23) * dt2;
      auto rel = [&](uint32_t e) {
        const float f = __uint_as_float((127u - min(em - e, 60u)) << 23);
        return packh(f, f);
      };
      const uint32_t r0 = rel(l0.x), r1 = rel(l0.y), r2 = rel(l0.z), r3 = rel(l0.w);
      auto sum4 = [&](uint32_t o, uint32_t sa, uint32_t a, uint32_t b, uint32_t c, uint32_t d) {
        const float2 x = unpackh(hfma2(a, r0, hfma2(b, r1, hfma2(c, r2, hmul2(d, r3)))));
        sts32(o, __float_as_uint(x.x * sc));
        sts32(o + sa, __float_as_uint(x.y * sc));
      };
      const uint32_t ib = sb + kOffI + w * kIChan;
      const uint32_t o0 = ib + (1 + q + 8 * r) * 4, o2 = ib + (513 + 32 * q + r) * 4;
      const uint32_t o1 = ib + (q < 2 ? 257 + q + 4 * r : 257 + 64 * q + 2 * r) * 4, s1 = q < 2 ? 128 : 64;
      if (lane == 0) sts32(ib, __float_as_uint(k0));
#pragma unroll
      for (int i = 0; i < 2; i++) {
        const uint32_t a = vb + i * 512 + lane * 16, o = i ? o1 : o0, st = i ? s1 : 256;
        const uint4 p0 = lds128(a), p1 = lds128(a + kPart), p2 = lds128(a + 2 * kPart), p3 = lds128(a + 3 * kPart);
        sum4(o, st >> 4, p0.x, p1.x, p2.x, p3.x);
        sum4(o + st, st >> 4, p0.y, p1.y, p2.y, p3.y);
        sum4(o + 2 * st, st >> 4, p0.z, p1.z, p2.z, p3.z);
        sum4(o + 3 * st, st >> 4, p0.w, p1.w, p2.w, p3.w);
      }
      {
        const uint32_t a = vb + 1024 + lane * 8;
        const uint2 p0 = lds64(a), p1 = lds64(a + kPart), p2 = lds64(a + 2 * kPart), p3 = lds64(a + 3 * kPart);
        sum4(o2, 64, p0.x, p1.x, p2.x, p3.x);
        sum4(o2 + 32, 64, p0.y, p1.y, p2.y, p3.y);
      }
      __syncwarp();
#pragma unroll
      for (int i = 0; i < 5; i++) {
        const uint4 p = lds128(ib + i * 512 + lane * 16);
        k[i][0] = __uint_as_float(p.x); k[i][1] = __uint_as_float(p.y);
        k[i][2] = __uint_as_float(p.z); k[i][3] = __uint_as_float(p.w);
      }
      const float k2048 = __uint_as_float(lds32v(ib + 2560));
      const bool first = lane == 0, last = lane == 31;
      const int up = (lane + 31) & 31, dn = (lane + 1) & 31;
      auto sh = [&](float v, int src) { return __shfl_sync(0xffffffffu, v, src); };
      const float u0 = sh(k[0][3], up), u1 = sh(k[1][3], up);
      const float n2 = sh(k[2][0], dn), n3 = sh(k[3][0], dn), n4 = sh(k[4][0], dn);
      const float u31 = sh(k[3][1], up), u32 = sh(k[3][2], up), u33 = sh(k[3][3], up), u43 = sh(k[4][3], up);
      k512 = __shfl_sync(0xffffffffu, pack2(k[3][0], k[3][0]), 0);
      k1024 = __shfl_sync(0xffffffffu, pack2(k[4][0], k[4][0]), 0);
      sts128(tb + 64 + lane * 16, pack2(k[0][0], first ? 0.f : u0), pack2(k[0][1], k[0][0]), pack2(k[0][2], k[0][1]), pack2(k[0][3], k[0][2]));
      sts128(tb + 576 + lane * 16, pack2(k[1][0], first ? u0 : u1), pack2(k[1][1], k[1][0]), pack2(k[1][2], k[1][1]), pack2(k[1][3], k[1][2]));
      sts128(tb + 1088 + lane * 32, pack2(k[2][0], first ? u1 : k[2][0]), pack2(k[2][0], k[2][0]), pack2(k[2][1], k[2][0]), pack2(k[2][2], k[2][1]));
      sts128(tb + 1104 + lane * 32, pack2(k[2][2], k[2][2]), pack2(k[2][2], k[2][2]), pack2(k[2][3], k[2][2]), pack2(last ? n3 : n2, k[2][3]));
      if (lane < 4) {
        sts128(tb + lane * 16, 0u, 0u, 0u, 0u);
        sts128(tb + 2112 + lane * 16, first ? pack2(k[3][0], k[3][0]) : 0u, first ? pack2(0.f, k[3][0]) : 0u, 0u, 0u);
        sts128(tb + kTapA + lane * 16, 0u, 0u, 0u, 0u);
        sts128(tb + kTapB + lane * 16, 0u, 0u, 0u, 0u);
        sts128(tb + kTapC + lane * 16, 0u, 0u, 0u, 0u);
        sts128(tb + kTapA + 320 + lane * 16, first ? pack2(0.f, u31) : 0u, first ? pack2(0.f, u32) : 0u, 0u, 0u);
        sts128(tb + kTapB + 320 + lane * 16, first ? pack2(0.f, u33) : 0u, first ? pack2(0.f, k[4][0]) : 0u, 0u, 0u);
      }
      sts64(tb + kTapA + 64 + lane * 8, pack2(k[3][1], first ? 0.f : u31), pack2(k[3][2], first ? 0.f : u32));
      sts64(tb + kTapB + 64 + lane * 8, pack2(k[3][3], first ? 0.f : u33), pack2(last ? n4 : n3, first ? 0.f : k[3][0]));
      sts128(tb + kTapC + 64 + lane * 16, pack2(k[4][1], first ? 0.f : u43), pack2(k[4][2], first ? 0.f : k[4][0]),
             pack2(k[4][3], k[4][1]), pack2(last ? k2048 : n4, k[4][2]));
      __syncwarp();
    }
    {
      auto chunk = [&](int row, int h) { return ub + row * 128 + (((2 * w + h) ^ (row & 7)) << 4); };
      const uint32_t a0 = chunk(lane + 6, 1) + 8, a1 = chunk(lane + 7, 0), a2 = chunk(lane + 8, 0);
      const uint32_t ov = vb + lane * 16, oi = sb + kOffI + w * kIChan + lane * 16;
      mbar_wait(bars + B_U * 8, 0);
      uint32_t y[8] = {0u, 0u, 0u, 0u, 0u, 0u, 0u, 0u};
#pragma unroll
      for (int it = 0; it < 3; it++) {
        const uint2 c0 = lds64(a0 + it * 4096);
        const uint4 c1 = lds128(a1 + it * 4096), c2 = lds128((a1 ^ 16) + it * 4096);
        const uint4 c3 = lds128(a2 + it * 4096), c4 = lds128((a2 ^ 16) + it * 4096);
        const uint32_t e[18] = {c0.x, c0.y, c1.x, c1.y, c1.z, c1.w, c2.x, c2.y, c2.z, c2.w,
                                c3.x, c3.y, c3.z, c3.w, c4.x, c4.y, c4.z, c4.w};
        uint32_t o[17], b[17], qd[15], r3[16], w5[15];
#pragma unroll
        for (int j = 0; j < 17; j++) {
          o[j] = __byte_perm(e[j], e[j + 1], 0x5432);
          b[j] = badd2(o[j], e[j]);
          if (j >= 1 && j < 15) qd[j] = badd2(b[j], b[j - 1]);
          if (j >= 5 && j < 16) r3[j] = badd2(b[j], o[j - 1]);
          if (j >= 4 && j < 15) w5[j] = badd2(qd[j - 1], e[j]);
        }
#pragma unroll
        for (int h = 0; h < 8; h += 4) {
          if (it < 2) {
            sts128(ov + it * 512 + kV9e + h * 256, badd2(w5[h + 4], qd[h + 1]), badd2(w5[h + 5], qd[h + 2]),
                   badd2(w5[h + 6], qd[h + 3]), badd2(w5[h + 7], qd[h + 4]));
            sts128(ov + it * 512 + kV7e + h * 256, badd2(qd[h + 7], r3[h + 5]), badd2(qd[h + 8], r3[h + 6]),
                   badd2(qd[h + 9], r3[h + 7]), badd2(qd[h + 10], r3[h + 8]));
          }
          sts128(ov + it * 512 + kV5e + h * 384, w5[h + 7], w5[h + 8], w5[h + 9], w5[h + 10]);
          sts128(ov + it * 512 + kV3e + h * 384, r3[h + 8], r3[h + 9], r3[h + 10], r3[h + 11]);
          sts128(oi + it * 512 + h * 384, bfma2(k512, b[h + 9], y[h]), bfma2(k512, b[h + 10], y[h + 1]),
                 bfma2(k512, b[h + 11], y[h + 2]), bfma2(k512, b[h + 12], y[h + 3]));
#pragma unroll
          for (int t = 0; t < 4; t++) y[h + t] = bmul2(k1024, b[h + t + 8]);
        }
      }
    }
    bar_arrive(NB_PREP, 256);
  } else {
    asm volatile("setmaxnreg.dec.sync.aligned.u32 24;");
    bar_arrive(NB_KGEN, kThreads);
    if (!early) asm volatile("barrier.cluster.wait.aligned;" ::: "memory");
    if (warp == 12) {
      if (elect()) {
        issue_p1(sb, 4, 16, &map_x, map_w, ft, tt, rank);
        if (full_cta) load_w<0>(sb, &map_wd, dt * 64);
      }
    } else if (warp == 13) {
      if (blk < 128) bar_sync(NB_GATE, 192);
      store_h(sb, 1, ft, tt);
      if (full_cta) {
        bar_sync(NB_AST, 160);
        if (elect()) {
          cnt_add(C_A + (cta >> 4), 1ull);
          cnt_wait(C_A + dt, 0xffull, 16ull);
          mbar_wait(bars + kBarA * 8, 0);
          tma2d(sb + kOffA, &map_a, tj * 128, dt * 64, bars + B_A * 8);
          mbar_arrive(bars + B_AP * 8);
          mbar_arrive(bars + B_AP * 8);
        }
        __syncwarp();
        bar_sync(NB_AST, 160);
        fence_async_smem();
        if (elect()) tma2d_store(&map_out, sb + kOffOut, dt * 64, tj * 128);
        bar_sync(NB_CONV, 160);
        fence_async_smem();
        if (elect()) {
          tma2d_store(&map_out, sb + kOffOut + 8192, dt * 64, tj * 128 + 64);
          bulk_commit();
          bulk_wait_read();
        }
      }
    } else if (warp == 14) {
      if (full_cta && elect()) {
        const int t0 = tj * 128 + rank * 64;
        const unsigned long long f = (1ull << (5 * (tj * 128 / kTok1))) | (1ull << (5 * ((tj * 128 + 127) / kTok1)));
        asm volatile("prefetch.tensormap [%0];" ::"l"(&map_ut) : "memory");
        asm volatile("prefetch.tensormap [%0];" ::"l"(&map_wd) : "memory");
        asm volatile("prefetch.tensormap [%0];" ::"l"(&map_a) : "memory");
        asm volatile("prefetch.tensormap [%0];" ::"l"(&map_out) : "memory");
        if ((sb & 0xffffffu) != kS) __trap();
#pragma unroll 1
        for (int k = 0; k < kNumFt + 3; k++) {
          const uint32_t bar = bars + (k < kNumFt ? B_FULL2 + k : k == kNumFt ? B_WR : k == kNumFt + 1 ? B_G : B_A) * 8;
          mbar_arrive(bar);
          mbar_expect(bar, k < kRegW || k == kNumFt + 2 ? 16384 : k < kNumFt ? 24576 : k == kNumFt ? kRegW * 8192 : 256);
        }
        mbar_wait(bars + B_RDYA1 * 8, 0);
        cnt_wait(C_H + 1, f * 31ull, f * 11ull);
        load_h<0>(sb, sb + rank * 8192, g_H + (size_t)t0 * 128, g_gate + tj * 128);
        mbar_wait(bars + B_AP * 8, 0);
        cnt_done();
      }
    } else {
      if (blk < 128) {
        bar_sync(NB_WG2, 160);
        if (elect()) cnt_add(C_U, 1ull);
        bar_sync(NB_GATE, 192);
      }
      if (full_cta && elect()) {
        cnt_wait(C_U, 0xffull, 128ull);
        mbar_expect(bars + B_U * 8, 17408);
        tma2d(sb + kOffU, &map_ut, cta * 64, -8, bars + B_U * 8);
      }
      __syncwarp();
      store_h(sb, 0, ft, tt);
      if (full_cta && elect()) {
        const unsigned long long f = (1ull << (5 * (tj * 128 / kTok1))) | (1ull << (5 * ((tj * 128 + 127) / kTok1)));
        cnt_wait(C_H, f * 31ull, f * 11ull);
        mbar_arrive(bars + B_H0 * 8);
        mbar_arrive(bars + B_H0 * 8);
      }
    }
  }
}

typedef CUresult (*EncodeFn)(CUtensorMap*, CUtensorMapDataType, cuuint32_t, void*, const cuuint64_t*, const cuuint64_t*,
                             const cuuint32_t*, const cuuint32_t*, CUtensorMapInterleave, CUtensorMapSwizzle,
                             CUtensorMapL2promotion, CUtensorMapFloatOOBfill);

void make_map(EncodeFn enc, CUtensorMap* m, const void* base, uint64_t cols, uint64_t rows, uint32_t bc, uint32_t br,
              CUtensorMapSwizzle sw) {
  const cuuint64_t dims[2] = {cols, rows}, strides[1] = {cols * 2};
  const cuuint32_t box[2] = {bc, br}, es[2] = {1, 1};
  enc(m, CU_TENSOR_MAP_DATA_TYPE_BFLOAT16, 2, const_cast<void*>(base), dims, strides, box, es,
      CU_TENSOR_MAP_INTERLEAVE_NONE, sw, CU_TENSOR_MAP_L2_PROMOTION_L2_128B, CU_TENSOR_MAP_FLOAT_OOB_FILL_NONE);
}

}

extern "C" void kernel_launch(void* const* d_in, const int* in_sizes, int n_in, void* d_out, int out_size) {
  (void)in_sizes; (void)n_in; (void)out_size;
  static EncodeFn enc = nullptr;
  static void *ut = nullptr, *at_ = nullptr;
  if (!enc) {
    cudaDriverEntryPointQueryResult qr;
    cudaGetDriverEntryPoint("cuTensorMapEncodeTiled", (void**)&enc, cudaEnableDefault, &qr);
    cudaGetSymbolAddress(&ut, g_uT);
    cudaGetSymbolAddress(&at_, g_aT);
    cudaFuncSetAttribute(fused_kernel, cudaFuncAttributeMaxDynamicSharedMemorySize, kSmemBytes);
  }
  CUtensorMap mx, mg, mu, md, mt, mo, mr, ma;
  make_map(enc, &mx, d_in[0], kD, kL, 32, kTok1, CU_TENSOR_MAP_SWIZZLE_64B);
  make_map(enc, &mg, d_in[8], kF, kD, 64, 32, CU_TENSOR_MAP_SWIZZLE_128B);
  make_map(enc, &mu, d_in[9], kF, kD, 64, 32, CU_TENSOR_MAP_SWIZZLE_128B);
  make_map(enc, &md, d_in[10], kD, kF, 64, 64, CU_TENSOR_MAP_SWIZZLE_128B);
  make_map(enc, &mt, ut, 8192, 128, 64, 136, CU_TENSOR_MAP_SWIZZLE_128B);
  make_map(enc, &ma, at_, kL, kD, 128, 64, CU_TENSOR_MAP_SWIZZLE_NONE);
  make_map(enc, &mo, d_out, kD, kL, 64, 64, CU_TENSOR_MAP_SWIZZLE_128B);
  {
    const cuuint64_t dims[3] = {64, kL, 8}, strides[2] = {kD * 2, 128};
    const cuuint32_t box[3] = {64, 16, 8}, es[3] = {1, 1, 1};
    enc(&mr, CU_TENSOR_MAP_DATA_TYPE_BFLOAT16, 3, d_in[0], dims, strides, box, es, CU_TENSOR_MAP_INTERLEAVE_NONE,
        CU_TENSOR_MAP_SWIZZLE_128B, CU_TENSOR_MAP_L2_PROMOTION_L2_128B, CU_TENSOR_MAP_FLOAT_OOB_FILL_NONE);
  }
  Params p;
  p.log_a = (const __nv_bfloat16*)d_in[1];
  p.a_im = (const __nv_bfloat16*)d_in[2];
  p.c_re = (const __nv_bfloat16*)d_in[3];
  p.c_im = (const __nv_bfloat16*)d_in[4];
  p.log_dt = (const __nv_bfloat16*)d_in[5];
  p.d_skip = (const __nv_bfloat16*)d_in[6];
  p.gate_w = (const __nv_bfloat16*)d_in[11];

  fused_kernel<<<132, kThreads, kSmemBytes, cudaStreamPerThread>>>(p, mx, mg, mu, md, mt, mo, mr, ma);
}
```
